```python
import torch

def _softmax(x, axis=-1):
    return torch.softmax(x, dim=axis)

def _gelu(x):
    return torch.nn.functional.gelu(x, approximate='tanh')

def _silu(x):
    return torch.nn.functional.silu(x)

def _sigmoid(x):
    return torch.sigmoid(x)

def _layernorm(x, axis=-1, eps=1e-05):
    m = x.mean(dim=axis, keepdim=True)
    v = x.var(dim=axis, keepdim=True, unbiased=False)
    return (x - m) / torch.sqrt(v + eps)

def _scatter_add(tgt, idx, src, axis=0):
    return tgt.clone().index_add_(axis, idx, src)

def _segment_sum(src, seg, n):
    out = torch.zeros((n,) + src.shape[1:], dtype=src.dtype)
    return out.index_add_(0, seg, src)

def _pad(x, pw):
    flat = tuple((v for pair in reversed(pw) for v in pair))
    return torch.nn.functional.pad(x, flat)
kernel_name = 'adaLN_cond__sliding_block__glu_gated_reglu__prompt'

def setup_inputs():

    _w = lambda a: (lambda t: t.to(torch.bfloat16) if t.is_floating_point() else t)(torch.as_tensor(a))

    def _A_setup():
        B, S, D = (1, 2048, 448)
        return {'x': _w((lambda *s: torch.randn(*s, dtype=torch.bfloat16) * 0.05)(B, S, D)), 'wqkv': _w((lambda *s: torch.randn(*s, dtype=torch.bfloat16) * 0.05)(D, 3 * D)), 'wo': _w((lambda *s: torch.randn(*s, dtype=torch.bfloat16) * 0.05)(D, D))}
    _A_in = _A_setup()

    def _B_setup():
        B, S, D, F = (1, 2048, 448, 1792)
        return {'x': _w((lambda *s: torch.randn(*s, dtype=torch.bfloat16) * 0.05)(B, S, D)), 'W_gate': _w((lambda *s: torch.randn(*s, dtype=torch.bfloat16) * 0.8)(D, F) * (2.0 / D) ** 0.5), 'W_up': _w((lambda *s: torch.randn(*s, dtype=torch.bfloat16) * 0.8)(D, F) * (2.0 / D) ** 0.5), 'W_down': _w((lambda *s: torch.randn(*s, dtype=torch.bfloat16) * 0.8)(F, D) * (1.0 / F) ** 0.5)}
    _B_in = _B_setup()
    return {'A_x': _A_in['x'], 'A_wqkv': _A_in['wqkv'], 'A_wo': _A_in['wo'], 'B_x': _B_in['x'], 'B_W_gate': _B_in['W_gate'], 'B_W_up': _B_in['W_up'], 'B_W_down': _B_in['W_down'], 'c': _w((lambda *s: torch.randn(*s, dtype=torch.bfloat16) * 0.1)(1, 448) * 8.0), 'w_mod': _w((lambda *s: torch.randn(*s, dtype=torch.bfloat16) * 0.1)(448, 6 * 448) * 448 ** (-0.5) * 8.0)}

def reference(A_x, A_wqkv, A_wo, B_x, B_W_gate, B_W_up, B_W_down, c, w_mod):

    def _A_ref(x, wqkv, wo):
        B, S, D = x.shape
        H = 16
        Dh = D // H
        W = 256
        qkv = (lambda x, *d: x.permute(*d))((x @ wqkv).reshape(B, S, 3, H, Dh), 2, 0, 3, 1, 4)
        q, k, v = (qkv[0], qkv[1], qkv[2])
        scores = torch.einsum('bhqd,bhkd->bhqk', q, k) * Dh ** (-0.5)
        idx = torch.arange(S)
        mask = (idx[:, None] - idx[None, :] >= 0) & (idx[:, None] - idx[None, :] < W)
        scores = torch.where(mask[None, None], scores, -1000000000.0)
        p = _softmax(scores, axis=-1)
        o = torch.einsum('bhqk,bhkd->bhqd', p, v)
        return (lambda x, *d: x.permute(*d))(o, 0, 2, 1, 3).reshape(B, S, D) @ wo

    def _B_ref(x, W_gate, W_up, W_down):
        gate = torch.einsum('bsd,df->bsf', x, W_gate)
        up = torch.einsum('bsd,df->bsf', x, W_up)
        gate = gate * (lambda x, dt: x.to(dt))(gate > 0, gate.dtype)
        h = gate * up
        return torch.einsum('bsf,fd->bsd', h, W_down)
    x = A_x
    mod = (_silu(c) @ w_mod).reshape(c.shape[0], 6, 1, -1)
    sa, ca, ga, sb, cb, gb = (mod[:, 0].clone(), mod[:, 1].clone(), mod[:, 2].clone(), mod[:, 3].clone(), mod[:, 4].clone(), mod[:, 5].clone())
    h = _layernorm(x, axis=-1) * (1 + ca) + sa
    x = x + ga * _A_ref(h, A_wqkv, A_wo)
    h = _layernorm(x, axis=-1) * (1 + cb) + sb
    x = x + gb * _B_ref(h, B_W_gate, B_W_up, B_W_down)
    return x
```

```cpp
#include <cuda_runtime.h>
#include <cuda_bf16.h>
#include <cuda.h>
#include <stdint.h>

#define DBG_TIMING 0

namespace {

constexpr int SEQ = 2048, DM = 448, FF = 1792;
constexpr int NCTA = 128;
constexpr int NTHREADS = 384;
constexpr uint32_t SLOT = 28672;
constexpr int NSLOT = 7;
constexpr uint32_t KVT = 7168;
constexpr uint32_t OFF_QX = NSLOT * SLOT;
constexpr uint32_t OFF_C1 = OFF_QX + 24576;
constexpr uint32_t OFF_S1 = OFF_C1 + 896;
constexpr uint32_t OFF_C2 = OFF_S1 + 896;
constexpr uint32_t OFF_S2 = OFF_C2 + 896;
constexpr uint32_t OFF_GA = OFF_S2 + 896;
constexpr uint32_t OFF_GB = OFF_GA + 128;
constexpr uint32_t OFF_RED = OFF_GB + 128;
constexpr uint32_t OFF_BAR = OFF_RED + 1024;
enum { F_X0, F_K0 = F_X0 + 2, F_K1, F_V0, F_V1, F_Q0, F_Q1, F_HK, F_HV, F_WO0, F_WO1, F_O0, F_O1, F_Y0, F_Y1, F_MOD2, F_WM, R_WM, T_TOK, F_RING = T_TOK + 8,
       N_ONE = F_RING + NSLOT,
       R_X = N_ONE, R_K, R_V, R_Q, R_ATT, R_WO, R_KST, R_VST, E_RING,
       N_EIGHT = E_RING + NSLOT,
       R_O0 = N_EIGHT, R_O1, R_Y0, R_Y1, N_BARS };
constexpr uint32_t SMEM_BYTES = OFF_BAR + 8 * N_BARS;
constexpr uint32_t SB = 0x400;
__host__ __device__ constexpr uint32_t BAR(int i) { return SB + OFF_BAR + 8 * i; }
__host__ __device__ constexpr uint32_t SLOTA(int i) { return SB + i * SLOT; }
__host__ __device__ constexpr int ring_slot(int i) { return i == 0 ? 6 : (i < 5 ? i + 1 : i - 5); }

constexpr int SPIN_LIMIT = 1 << 17;

struct Scratch {
    uint4 part[32 * 8 * 8 * 4 * 128];
    uint4 o[32 * 8 * 4 * 128];
    uint4 x2[32 * 8 * 4 * 128];
    uint4 st2[32 * 8 * 64];
    uint8_t kv[16 * 8 * 2 * 2 * KVT];
    uint4 modp[4 * 224];
    uint2 mod[1344];
    uint32_t kvflag[16 * 8 * 2 * 8];
    uint32_t epoch[NCTA * 32];
};
__device__ __align__(1024) Scratch g_scr;

__device__ __forceinline__ uint32_t smem_u32(const void* p) { return (uint32_t)__cvta_generic_to_shared(p); }
__device__ __forceinline__ void mbar_init(uint32_t bar, uint32_t cnt) {
    asm volatile("mbarrier.init.shared::cta.b64 [%0], %1;" ::"r"(bar), "r"(cnt) : "memory");
}
__device__ __forceinline__ void mbar_arrive(uint32_t bar) {
    asm volatile("mbarrier.arrive.shared::cta.b64 _, [%0];" ::"r"(bar) : "memory");
}
__device__ __forceinline__ void mbar_expect_tx(uint32_t bar, uint32_t bytes) {
    asm volatile("mbarrier.arrive.expect_tx.shared::cta.b64 _, [%0], %1;" ::"r"(bar), "r"(bytes) : "memory");
}
__device__ __forceinline__ void mbar_wait(uint32_t bar, uint32_t parity) {
    uint32_t done;
    int it = 0;
#pragma unroll 1
    do {
        asm volatile("{\n.reg .pred p;\nmbarrier.try_wait.parity.shared::cta.b64 p, [%1], %2;\nselp.u32 %0, 1, 0, p;\n}\n"
                     : "=r"(done) : "r"(bar), "r"(parity) : "memory");
        if (++it > SPIN_LIMIT) break;
    } while (!done);
}
__device__ __forceinline__ void tma_2d(uint32_t dst, const CUtensorMap* m, int c0, int c1, uint32_t bar) {
    asm volatile("cp.async.bulk.tensor.2d.shared::cluster.global.mbarrier::complete_tx::bytes [%0], [%1, {%3, %4}], [%2];"
                 ::"r"(dst), "l"(m), "r"(bar), "r"(c0), "r"(c1) : "memory");
}
__device__ __forceinline__ void bulk_g2s(uint32_t dst, const void* src, uint32_t bytes, uint32_t bar) {
    asm volatile("cp.async.bulk.shared::cluster.global.mbarrier::complete_tx::bytes [%0], [%1], %2, [%3];"
                 ::"r"(dst), "l"(src), "r"(bytes), "r"(bar) : "memory");
}
__device__ __forceinline__ void bulk_s2g(void* dst, uint32_t src, uint32_t bytes) {
    asm volatile("cp.async.bulk.global.shared::cta.bulk_group [%0], [%1], %2;" ::"l"(dst), "r"(src), "r"(bytes) : "memory");
}
__device__ __forceinline__ void l2_prefetch(const void* src, uint32_t bytes) {
    asm volatile("cp.async.bulk.prefetch.L2.global [%0], %1;" ::"l"(src), "r"(bytes) : "memory");
}
__device__ __forceinline__ uint4 ld_rlx128(const uint4* p) {
    uint4 v;
    asm volatile("ld.relaxed.gpu.global.v4.u32 {%0,%1,%2,%3}, [%4];" : "=r"(v.x), "=r"(v.y), "=r"(v.z), "=r"(v.w) : "l"(p) : "memory");
    return v;
}
__device__ __forceinline__ void st_rlx128(uint4* p, uint32_t x, uint32_t y, uint32_t z, uint32_t w) {
    asm volatile("st.relaxed.gpu.global.v4.u32 [%0], {%1,%2,%3,%4};" ::"l"(p), "r"(x), "r"(y), "r"(z), "r"(w) : "memory");
}
__device__ __forceinline__ uint2 ld_rlx64(const uint2* p) {
    uint2 v;
    asm volatile("ld.relaxed.gpu.global.v2.u32 {%0,%1}, [%2];" : "=r"(v.x), "=r"(v.y) : "l"(p) : "memory");
    return v;
}
__device__ __forceinline__ void st_rlx64(uint2* p, uint32_t x, uint32_t y) {
    asm volatile("st.relaxed.gpu.global.v2.u32 [%0], {%1,%2};" ::"l"(p), "r"(x), "r"(y) : "memory");
}
__device__ __forceinline__ uint4 ldg128(const void* p) {
    uint4 v;
    asm volatile("ld.global.nc.L1::no_allocate.v4.u32 {%0,%1,%2,%3}, [%4];" : "=r"(v.x), "=r"(v.y), "=r"(v.z), "=r"(v.w) : "l"(p));
    return v;
}
__device__ __forceinline__ uint4 lds128(uint32_t a) {
    uint4 v;
    asm volatile("ld.shared.v4.u32 {%0,%1,%2,%3}, [%4];" : "=r"(v.x), "=r"(v.y), "=r"(v.z), "=r"(v.w) : "r"(a) : "memory");
    return v;
}
__device__ __forceinline__ uint32_t lds32(uint32_t a) {
    uint32_t v;
    asm volatile("ld.shared.u32 %0, [%1];" : "=r"(v) : "r"(a) : "memory");
    return v;
}
__device__ __forceinline__ void sts128(uint32_t a, uint32_t x, uint32_t y, uint32_t z, uint32_t w) {
    asm volatile("st.shared.v4.u32 [%0], {%1,%2,%3,%4};" ::"r"(a), "r"(x), "r"(y), "r"(z), "r"(w) : "memory");
}
__device__ __forceinline__ void sts32(uint32_t a, uint32_t x) { asm volatile("st.shared.u32 [%0], %1;" ::"r"(a), "r"(x) : "memory"); }
__device__ __forceinline__ void stsm4(uint32_t a, uint32_t r0, uint32_t r1, uint32_t r2, uint32_t r3) {
    asm volatile("stmatrix.sync.aligned.m8n8.x4.shared.b16 [%0], {%1,%2,%3,%4};" ::"r"(a), "r"(r0), "r"(r1), "r"(r2), "r"(r3) : "memory");
}
__device__ __forceinline__ void stsm2(uint32_t a, uint32_t r0, uint32_t r1) {
    asm volatile("stmatrix.sync.aligned.m8n8.x2.shared.b16 [%0], {%1,%2};" ::"r"(a), "r"(r0), "r"(r1) : "memory");
}
__device__ __forceinline__ void ldsm4(uint32_t (&r)[4], uint32_t a) {
    asm volatile("ldmatrix.sync.aligned.m8n8.x4.shared.b16 {%0,%1,%2,%3}, [%4];"
                 : "=r"(r[0]), "=r"(r[1]), "=r"(r[2]), "=r"(r[3]) : "r"(a) : "memory");
}
__device__ __forceinline__ void hmma(float (&c)[4], const uint32_t (&a)[4], uint32_t b0, uint32_t b1) {
    asm volatile("mma.sync.aligned.m16n8k16.row.col.f32.bf16.bf16.f32 {%0,%1,%2,%3}, {%4,%5,%6,%7}, {%8,%9}, {%0,%1,%2,%3};"
                 : "+f"(c[0]), "+f"(c[1]), "+f"(c[2]), "+f"(c[3])
                 : "r"(a[0]), "r"(a[1]), "r"(a[2]), "r"(a[3]), "r"(b0), "r"(b1));
}
__device__ __forceinline__ uint32_t ld_rlx32(const void* p) {
    uint32_t v;
    asm volatile("ld.relaxed.gpu.global.u32 %0, [%1];" : "=r"(v) : "l"(p) : "memory");
    return v;
}
__device__ __forceinline__ uint32_t pack2(float lo, float hi) {
    uint32_t r;
    asm("cvt.rn.bf16x2.f32 %0, %1, %2;" : "=r"(r) : "f"(hi), "f"(lo));
    return r;
}
__device__ __forceinline__ float bf_lo(uint32_t v) { return __uint_as_float(v << 16); }
__device__ __forceinline__ float bf_hi(uint32_t v) { return __uint_as_float(v & 0xFFFF0000u); }
__device__ __forceinline__ uint32_t hfma2(uint32_t a, uint32_t b, uint32_t c) {
    uint32_t r;
    asm("fma.rn.bf16x2 %0, %1, %2, %3;" : "=r"(r) : "r"(a), "r"(b), "r"(c));
    return r;
}
__device__ __forceinline__ uint32_t prmt(uint32_t a, uint32_t b, uint32_t sel) {
    uint32_t r;
    asm("prmt.b32 %0, %1, %2, %3;" : "=r"(r) : "r"(a), "r"(b), "r"(sel));
    return r;
}
__device__ __forceinline__ float ex2f(float x) {
    float r;
    asm("ex2.approx.ftz.f32 %0, %1;" : "=f"(r) : "f"(x));
    return r;
}
__device__ __forceinline__ float silu_bf(float v) {
    float s = __fdividef(v, 1.0f + __expf(-v));
    return bf_lo(pack2(s, 0.f));
}
__device__ __forceinline__ void bar_sync(int id, int n) { asm volatile("bar.sync %0, %1;" ::"r"(id), "r"(n) : "memory"); }
__device__ __forceinline__ void bar_arrive(int id, int n) { asm volatile("bar.arrive %0, %1;" ::"r"(id), "r"(n) : "memory"); }
__device__ __forceinline__ void fence_async_smem() { asm volatile("fence.proxy.async.shared::cta;" ::: "memory"); }
__device__ __forceinline__ uint64_t mk_desc(uint32_t addr, uint32_t lbo, uint32_t sbo, uint32_t swz) {
    const uint32_t lo = (addr >> 4) + ((lbo >> 4) << 16);
    const uint32_t hi = (sbo >> 4) | (swz << 30);
    return ((uint64_t)hi << 32) | lo;
}
#define WG_FENCE() asm volatile("wgmma.fence.sync.aligned;" ::: "memory")
#define WG_COMMIT() asm volatile("wgmma.commit_group.sync.aligned;" ::: "memory")
#define WG_WAIT(n) asm volatile("wgmma.wait_group.sync.aligned %0;" ::"n"(n) : "memory")
template <int N> __device__ __forceinline__ void pin(float (&d)[N]) {
#pragma unroll
    for (int i = 0; i < N; i++) asm volatile("" : "+f"(d[i])::"memory");
}
__device__ __forceinline__ void pin(uint32_t (&a)[4]) {
    asm volatile("" : "+r"(a[0]), "+r"(a[1]), "+r"(a[2]), "+r"(a[3])::"memory");
}

__device__ __forceinline__ void wgmma_n32_t1(float (&d)[16], const uint32_t (&a)[4], uint64_t descB, int scaleD) {
    asm volatile("{\n.reg .pred p;\nsetp.ne.b32 p, %21, 0;\n"
        "wgmma.mma_async.sync.aligned.m64n32k16.f32.bf16.bf16 "
        "{%0, %1, %2, %3, %4, %5, %6, %7, %8, %9, %10, %11, %12, %13, %14, %15}, "
        "{%16, %17, %18, %19}, %20, p, 1, 1, 1;\n}\n"
        : "+f"(d[0]), "+f"(d[1]), "+f"(d[2]), "+f"(d[3]), "+f"(d[4]), "+f"(d[5]), "+f"(d[6]), "+f"(d[7]),
          "+f"(d[8]), "+f"(d[9]), "+f"(d[10]), "+f"(d[11]), "+f"(d[12]), "+f"(d[13]), "+f"(d[14]), "+f"(d[15])
        : "r"(a[0]), "r"(a[1]), "r"(a[2]), "r"(a[3]), "l"(descB), "r"(scaleD));
}
__device__ __forceinline__ void wgmma_n56_t1(float (&d)[28], const uint32_t (&a)[4], uint64_t descB, int scaleD) {
    asm volatile("{\n.reg .pred p;\nsetp.ne.b32 p, %33, 0;\n"
        "wgmma.mma_async.sync.aligned.m64n56k16.f32.bf16.bf16 "
        "{%0, %1, %2, %3, %4, %5, %6, %7, %8, %9, %10, %11, %12, %13, %14, %15, "
        "%16, %17, %18, %19, %20, %21, %22, %23, %24, %25, %26, %27}, "
        "{%28, %29, %30, %31}, %32, p, 1, 1, 1;\n}\n"
        : "+f"(d[0]), "+f"(d[1]), "+f"(d[2]), "+f"(d[3]), "+f"(d[4]), "+f"(d[5]), "+f"(d[6]), "+f"(d[7]),
          "+f"(d[8]), "+f"(d[9]), "+f"(d[10]), "+f"(d[11]), "+f"(d[12]), "+f"(d[13]), "+f"(d[14]), "+f"(d[15]),
          "+f"(d[16]), "+f"(d[17]), "+f"(d[18]), "+f"(d[19]), "+f"(d[20]), "+f"(d[21]), "+f"(d[22]), "+f"(d[23]),
          "+f"(d[24]), "+f"(d[25]), "+f"(d[26]), "+f"(d[27])
        : "r"(a[0]), "r"(a[1]), "r"(a[2]), "r"(a[3]), "l"(descB), "r"(scaleD));
}
__device__ __forceinline__ void wgmma_n64_t0(float (&d)[32], const uint32_t (&a)[4], uint64_t descB, int scaleD) {
    asm volatile("{\n.reg .pred p;\nsetp.ne.b32 p, %37, 0;\n"
        "wgmma.mma_async.sync.aligned.m64n64k16.f32.bf16.bf16 "
        "{%0, %1, %2, %3, %4, %5, %6, %7, %8, %9, %10, %11, %12, %13, %14, %15, "
        "%16, %17, %18, %19, %20, %21, %22, %23, %24, %25, %26, %27, %28, %29, %30, %31}, "
        "{%32, %33, %34, %35}, %36, p, 1, 1, 0;\n}\n"
        : "+f"(d[0]), "+f"(d[1]), "+f"(d[2]), "+f"(d[3]), "+f"(d[4]), "+f"(d[5]), "+f"(d[6]), "+f"(d[7]),
          "+f"(d[8]), "+f"(d[9]), "+f"(d[10]), "+f"(d[11]), "+f"(d[12]), "+f"(d[13]), "+f"(d[14]), "+f"(d[15]),
          "+f"(d[16]), "+f"(d[17]), "+f"(d[18]), "+f"(d[19]), "+f"(d[20]), "+f"(d[21]), "+f"(d[22]), "+f"(d[23]),
          "+f"(d[24]), "+f"(d[25]), "+f"(d[26]), "+f"(d[27]), "+f"(d[28]), "+f"(d[29]), "+f"(d[30]), "+f"(d[31])
        : "r"(a[0]), "r"(a[1]), "r"(a[2]), "r"(a[3]), "l"(descB), "r"(scaleD));
}
__device__ __forceinline__ void wgmma_n64_t1(float (&d)[32], const uint32_t (&a)[4], uint64_t descB, int scaleD) {
    asm volatile("{\n.reg .pred p;\nsetp.ne.b32 p, %37, 0;\n"
        "wgmma.mma_async.sync.aligned.m64n64k16.f32.bf16.bf16 "
        "{%0, %1, %2, %3, %4, %5, %6, %7, %8, %9, %10, %11, %12, %13, %14, %15, "
        "%16, %17, %18, %19, %20, %21, %22, %23, %24, %25, %26, %27, %28, %29, %30, %31}, "
        "{%32, %33, %34, %35}, %36, p, 1, 1, 1;\n}\n"
        : "+f"(d[0]), "+f"(d[1]), "+f"(d[2]), "+f"(d[3]), "+f"(d[4]), "+f"(d[5]), "+f"(d[6]), "+f"(d[7]),
          "+f"(d[8]), "+f"(d[9]), "+f"(d[10]), "+f"(d[11]), "+f"(d[12]), "+f"(d[13]), "+f"(d[14]), "+f"(d[15]),
          "+f"(d[16]), "+f"(d[17]), "+f"(d[18]), "+f"(d[19]), "+f"(d[20]), "+f"(d[21]), "+f"(d[22]), "+f"(d[23]),
          "+f"(d[24]), "+f"(d[25]), "+f"(d[26]), "+f"(d[27]), "+f"(d[28]), "+f"(d[29]), "+f"(d[30]), "+f"(d[31])
        : "r"(a[0]), "r"(a[1]), "r"(a[2]), "r"(a[3]), "l"(descB), "r"(scaleD));
}
__device__ __forceinline__ void wgmma_n128_t1(float (&d)[64], const uint32_t (&a)[4], uint64_t descB, int scaleD) {
    asm volatile("{\n.reg .pred p;\nsetp.ne.b32 p, %69, 0;\n"
        "wgmma.mma_async.sync.aligned.m64n128k16.f32.bf16.bf16 "
        "{%0, %1, %2, %3, %4, %5, %6, %7, %8, %9, %10, %11, %12, %13, %14, %15, "
        "%16, %17, %18, %19, %20, %21, %22, %23, %24, %25, %26, %27, %28, %29, %30, %31, "
        "%32, %33, %34, %35, %36, %37, %38, %39, %40, %41, %42, %43, %44, %45, %46, %47, "
        "%48, %49, %50, %51, %52, %53, %54, %55, %56, %57, %58, %59, %60, %61, %62, %63}, "
        "{%64, %65, %66, %67}, %68, p, 1, 1, 1;\n}\n"
        : "+f"(d[0]), "+f"(d[1]), "+f"(d[2]), "+f"(d[3]), "+f"(d[4]), "+f"(d[5]), "+f"(d[6]), "+f"(d[7]),
          "+f"(d[8]), "+f"(d[9]), "+f"(d[10]), "+f"(d[11]), "+f"(d[12]), "+f"(d[13]), "+f"(d[14]), "+f"(d[15]),
          "+f"(d[16]), "+f"(d[17]), "+f"(d[18]), "+f"(d[19]), "+f"(d[20]), "+f"(d[21]), "+f"(d[22]), "+f"(d[23]),
          "+f"(d[24]), "+f"(d[25]), "+f"(d[26]), "+f"(d[27]), "+f"(d[28]), "+f"(d[29]), "+f"(d[30]), "+f"(d[31]),
          "+f"(d[32]), "+f"(d[33]), "+f"(d[34]), "+f"(d[35]), "+f"(d[36]), "+f"(d[37]), "+f"(d[38]), "+f"(d[39]),
          "+f"(d[40]), "+f"(d[41]), "+f"(d[42]), "+f"(d[43]), "+f"(d[44]), "+f"(d[45]), "+f"(d[46]), "+f"(d[47]),
          "+f"(d[48]), "+f"(d[49]), "+f"(d[50]), "+f"(d[51]), "+f"(d[52]), "+f"(d[53]), "+f"(d[54]), "+f"(d[55]),
          "+f"(d[56]), "+f"(d[57]), "+f"(d[58]), "+f"(d[59]), "+f"(d[60]), "+f"(d[61]), "+f"(d[62]), "+f"(d[63])
        : "r"(a[0]), "r"(a[1]), "r"(a[2]), "r"(a[3]), "l"(descB), "r"(scaleD));
}

#define TG(k) do {} while (0)
#define TS(k) do {} while (0)

__device__ __forceinline__ void publish14(uint4* dst, const uint32_t (&r)[14], uint32_t tag) {
    st_rlx128(dst + 0 * 128, r[0], r[1], r[2], prmt(r[3], tag, 0x1054));
    st_rlx128(dst + 1 * 128, r[4], r[5], r[6], prmt(r[7], tag, 0x1054));
    st_rlx128(dst + 2 * 128, r[8], r[9], r[10], prmt(r[11], tag, 0x1054));
    st_rlx128(dst + 3 * 128, r[12], r[13], prmt(r[3], r[7], 0x7632), prmt(r[11], tag, 0x3254));
}
__device__ __forceinline__ uint32_t tag_bad(const uint4 (&v)[4], uint32_t tag) {
    return ((v[0].w ^ tag) | (v[1].w ^ tag) | (v[2].w ^ tag) | (v[3].w ^ tag)) & 0xFFFFu;
}
__device__ __forceinline__ void unpack14(const uint4 (&v)[4], uint32_t (&r)[14]) {
    r[0] = v[0].x; r[1] = v[0].y; r[2] = v[0].z; r[3] = prmt(v[0].w, v[3].z, 0x5432);
    r[4] = v[1].x; r[5] = v[1].y; r[6] = v[1].z; r[7] = prmt(v[1].w, v[3].z, 0x7632);
    r[8] = v[2].x; r[9] = v[2].y; r[10] = v[2].z; r[11] = prmt(v[2].w, v[3].w, 0x7632);
    r[12] = v[3].x; r[13] = v[3].y;
}
template <int ODD> __host__ __device__ constexpr int kstep_group(int s) {
    return s == 6 ? ODD : (s / 3) * 7 + 2 * (s % 3) + (2 * (s % 3) >= ODD ? 1 : 0);
}
__host__ __device__ constexpr int kstep_gap(int s) { return s == 6 ? 7 : 1; }
__device__ __forceinline__ bool gather_try(uint4 (&v)[8][4], const uint4* src, uint32_t tag) {
#pragma unroll
    for (int s = 0; s < 8; s++)
#pragma unroll
        for (int k = 0; k < 4; k++) v[s][k] = ld_rlx128(src + (s * 4 + k) * 128);
    uint32_t bad = 0;
#pragma unroll
    for (int s = 0; s < 8; s++) bad |= tag_bad(v[s], tag);
    return __any_sync(0xFFFFFFFFu, bad != 0);
}
__device__ __forceinline__ float reduce8(float (&a)[8], int lane) {
    {
        bool up = lane & 16;
#pragma unroll
        for (int i = 0; i < 4; i++) {
            float keep = up ? a[i + 4] : a[i], send = up ? a[i] : a[i + 4];
            a[i] = keep + __shfl_xor_sync(0xFFFFFFFFu, send, 16);
        }
    }
    {
        bool up = lane & 8;
#pragma unroll
        for (int i = 0; i < 2; i++) {
            float keep = up ? a[i + 2] : a[i], send = up ? a[i] : a[i + 2];
            a[i] = keep + __shfl_xor_sync(0xFFFFFFFFu, send, 8);
        }
    }
    {
        bool up = lane & 4;
        float keep = up ? a[1] : a[0], send = up ? a[0] : a[1];
        a[0] = keep + __shfl_xor_sync(0xFFFFFFFFu, send, 4);
    }
    return a[0];
}
__device__ __forceinline__ void fma8(float (&a)[8], float s, uint4 w) {
    a[0] = fmaf(s, bf_lo(w.x), a[0]); a[1] = fmaf(s, bf_hi(w.x), a[1]);
    a[2] = fmaf(s, bf_lo(w.y), a[2]); a[3] = fmaf(s, bf_hi(w.y), a[3]);
    a[4] = fmaf(s, bf_lo(w.z), a[4]); a[5] = fmaf(s, bf_hi(w.z), a[5]);
    a[6] = fmaf(s, bf_lo(w.w), a[6]); a[7] = fmaf(s, bf_hi(w.w), a[7]);
}
__device__ __forceinline__ float quad_sum(float v) {
    v += __shfl_xor_sync(0xFFFFFFFFu, v, 1);
    v += __shfl_xor_sync(0xFFFFFFFFu, v, 2);
    return v;
}
__device__ __forceinline__ float quad_max(float v) {
    v = fmaxf(v, __shfl_xor_sync(0xFFFFFFFFu, v, 1));
    v = fmaxf(v, __shfl_xor_sync(0xFFFFFFFFu, v, 2));
    return v;
}
__device__ __forceinline__ void store_kv(uint32_t tile_addr, const float (&acc)[28], int warp, int lane) {
    uint32_t a = tile_addr + (lane >> 4) * 1024 + (2 * warp + ((lane >> 3) & 1)) * 128 + (lane & 7) * 16;
#pragma unroll
    for (int i = 0; i < 3; i++)
        stsm4(a + i * 2048, pack2(acc[8 * i + 0], acc[8 * i + 1]), pack2(acc[8 * i + 2], acc[8 * i + 3]),
              pack2(acc[8 * i + 4], acc[8 * i + 5]), pack2(acc[8 * i + 6], acc[8 * i + 7]));
    uint32_t a2 = tile_addr + 6 * 1024 + (2 * warp + ((lane >> 3) & 1)) * 128 + (lane & 7) * 16;
    stsm2(a2, pack2(acc[24], acc[25]), pack2(acc[26], acc[27]));
}

#define TOKEN_KK 3
constexpr int N_GU3 = 0, N_GU = 2, N_DN = 14, N_ITEMS = 22;

__device__ __forceinline__ bool landed_read(uint4 (&v)[8][4], uint32_t main_addr, uint32_t ext_addr, uint32_t tag) {
#pragma unroll
    for (int s = 0; s < 8; s++)
#pragma unroll
        for (int k = 0; k < 4; k++) v[s][k] = lds128((s < 7 ? main_addr + s * 8192 : ext_addr) + k * 2048);
    uint32_t bad = 0;
#pragma unroll
    for (int s = 0; s < 8; s++) bad |= tag_bad(v[s], tag);
    return __any_sync(0xFFFFFFFFu, bad != 0);
}
__device__ __forceinline__ void gather_issue(const uint4* src, bool two, uint32_t tag, int lane, uint32_t main_addr, uint32_t ext_addr,
                                             uint32_t bar) {
    const uint32_t* p = (const uint32_t*)(src + ((lane >> 2) * 4 + 3) * 128 + (lane & 3) * 32 + 31) + 3;
    int it = 0;
#pragma unroll 1
    while (true) {
        uint32_t bad = ld_rlx32(p) ^ tag;
        if (two) bad |= ld_rlx32(p - 2 * 128 * 4) ^ tag;
        if (!__any_sync(0xFFFFFFFFu, (bad & 0xFFFFu) != 0)) break;
        if (++it > SPIN_LIMIT) break;
    }
    if (lane == 0) {
        mbar_expect_tx(bar, 65536);
        bulk_g2s(main_addr, src, 28672, bar);
        bulk_g2s(main_addr + 28672, (const uint8_t*)src + 28672, 28672, bar);
        bulk_g2s(ext_addr, (const uint8_t*)src + 57344, 8192, bar);
    }
    __syncwarp();
}
template <int A, int B> __device__ __forceinline__ void init_bars() {
#pragma unroll
    for (int i = A; i < B; i++) mbar_init(BAR(i), i < N_ONE ? 1 : (i < N_EIGHT ? 8 : 4));
}
__device__ __forceinline__ uint32_t perm_off(int p) {
    const int blk = p >> 2, q = p & 3;
    return ((blk >> 2) * 16 + q * 4 + (blk & 3)) * 4;
}

__global__ void __launch_bounds__(NTHREADS, 1)
fused_block_kernel(Scratch* __restrict__ scr, const __nv_bfloat16* __restrict__ x, const __nv_bfloat16* __restrict__ cvec,
                   const __nv_bfloat16* __restrict__ wmod, __nv_bfloat16* __restrict__ out, const __nv_bfloat16* __restrict__ wqkv, const __nv_bfloat16* __restrict__ wo,
                   const __nv_bfloat16* __restrict__ wg, const __nv_bfloat16* __restrict__ wu, const __nv_bfloat16* __restrict__ wd,
                   const __grid_constant__ CUtensorMap tm_x, const __grid_constant__ CUtensorMap tm_qkv,
                   const __grid_constant__ CUtensorMap tm_wo, const __grid_constant__ CUtensorMap tm_g,
                   const __grid_constant__ CUtensorMap tm_u, const __grid_constant__ CUtensorMap tm_g3,
                   const __grid_constant__ CUtensorMap tm_u3, const __grid_constant__ CUtensorMap tm_d,
                   const __grid_constant__ CUtensorMap tm_m) {
    extern __shared__ __align__(1024) uint8_t smem_raw[];
    const int bid = blockIdx.x;
    const int j = (bid & 3) + 4 * (bid >> 6);
    const int b = (bid & 63) >> 2;
    const int tid = threadIdx.x;
    const int lane = tid & 31;
    if (smem_u32(smem_raw) != SB) return;
    TS(0);
    TG(30);
    const int qcol = 56 * j - 8 * (j & 1);
    const int wgi = __shfl_sync(0xFFFFFFFFu, tid >> 7, 0);
    if (wgi == 2) {
        asm volatile("setmaxnreg.dec.sync.aligned.u32 40;");
        const int hw = __shfl_sync(0xFFFFFFFFu, (tid - 256) >> 5, 0);
        if (lane == 0) {
            if (hw == 0) {
                asm volatile("prefetch.tensormap [%0];" ::"l"(&tm_x) : "memory");
                asm volatile("prefetch.tensormap [%0];" ::"l"(&tm_qkv) : "memory");
                init_bars<0, F_HK>();
            }
            if (hw == 1) init_bars<F_HK, F_RING>();
            if (hw == 2) init_bars<F_RING, E_RING>();
            if (hw == 3) init_bars<E_RING, N_BARS>();
            asm volatile("fence.mbarrier_init.release.cluster;" ::: "memory");
        }
        __syncwarp();
        bar_arrive(2, 384);
        if (hw == 0) bar_arrive(3, 128);
        else { bar_arrive(7, 128); bar_sync(3, 128); }
        uint32_t tag = 0;
        if (hw != 0) tag = ld_rlx32(&scr->epoch[bid * 32 + lane]);
        if (hw == 0) {
            if (lane == 0) {
                TS(1);
                mbar_expect_tx(BAR(F_X0), 4 * 16384);
                mbar_expect_tx(BAR(F_X0 + 1), 3 * 16384);
#pragma unroll
                for (int c = 0; c < 7; c++) tma_2d(SLOTA(3) + c * 16384, &tm_x, 64 * c, 128 * b, BAR(F_X0 + (c >= 4)));
#pragma unroll
                for (int i = F_K0; i <= F_Q1; i++) mbar_expect_tx(BAR(i), SLOT);
                tma_2d(SLOTA(0), &tm_qkv, DM + qcol, 0, BAR(F_K0));
                tma_2d(SLOTA(1), &tm_qkv, DM + qcol, 224, BAR(F_K1));
                tma_2d(SLOTA(2), &tm_qkv, 2 * DM + qcol, 0, BAR(F_V0));
                TS(2);
            }
            bar_sync(7, 128);
            if (lane == 0) {
                mbar_wait(BAR(R_X), 0);
                tma_2d(SLOTA(3), &tm_qkv, 2 * DM + qcol, 224, BAR(F_V1));
                tma_2d(SLOTA(4), &tm_qkv, qcol, 0, BAR(F_Q0));
                tma_2d(SLOTA(5), &tm_qkv, qcol, 224, BAR(F_Q1));
                TS(3);
                mbar_wait(BAR(R_V), 0);
                mbar_expect_tx(BAR(F_WO0), SLOT);
                mbar_expect_tx(BAR(F_WO1), SLOT);
                mbar_wait(BAR(F_HV), 0);
                tma_2d(SLOTA(2), &tm_wo, qcol, 0, BAR(F_WO0));
                tma_2d(SLOTA(3), &tm_wo, qcol, 224, BAR(F_WO1));
                int pos = 0, use = 0;
#pragma unroll 1
                for (int n = 0; n < N_ITEMS; n++) {
                    const uint32_t full = BAR(F_RING) + 8 * pos;
                    const uint32_t dst = SB + ring_slot(pos) * SLOT;
                    if (use == 0) mbar_wait(BAR(n == 0 ? R_ATT : (n < 3 ? R_WO : (n < 5 ? R_Y0 : R_Y1))), 0);
                    else mbar_wait(BAR(E_RING) + 8 * pos, (use - 1) & 1);
                    mbar_expect_tx(full, SLOT);
                    if (n < N_GU) {
                        const int col = 224 * j + ((j & 1) ? 0 : 192), row = 224 * n;
                        tma_2d(dst, &tm_g3, col, row, full);
                        tma_2d(dst + SLOT / 2, &tm_u3, col, row, full);
                    } else if (n < N_DN) {
                        const int m = n - N_GU;
                        const int col = 224 * j + 32 * (j & 1) + 64 * (m >> 2), row = 112 * (m & 3);
                        tma_2d(dst, &tm_g, col, row, full);
                        tma_2d(dst + SLOT / 2, &tm_u, col, row, full);
                    } else {
                        const int sl = (j + 1 + (n - N_DN)) & 7;
                        tma_2d(dst, &tm_d, 56 * sl - 8 * (sl & 1), 224 * j, full);
                    }
                    if (++pos == NSLOT) { pos = 0; use++; }
                }
            }
            return;
        }
        if (hw == 1) {
            if (lane == 0) {
                mbar_wait(BAR(F_X0 + 1), 0);
                l2_prefetch((const uint8_t*)wqkv + bid * 9408, 9408);
                mbar_wait(BAR(F_V0), 0);
                l2_prefetch((const uint8_t*)wo + bid * 3136, 3136);
                l2_prefetch((const uint8_t*)wg + bid * 12544, 12544);
                l2_prefetch((const uint8_t*)wu + bid * 12544, 12544);
                l2_prefetch((const uint8_t*)wd + bid * 12544, 12544);
            }
            tag += 1;
            if (lane == 0) {
#pragma unroll 1
                for (int m = 0; m < 2; m++) {
                    mbar_wait(BAR(R_KST) + 8 * m, 0);
                    const int idx = (b * 8 + j) * 2 + m;
                    bulk_s2g(scr->kv + (size_t)idx * 2 * KVT, SLOTA(6) + m * 2 * KVT, 2 * KVT);
                    asm volatile("cp.async.bulk.commit_group;" ::: "memory");
                    asm volatile("cp.async.bulk.wait_group 0;" ::: "memory");
                    asm volatile("st.relaxed.gpu.global.u32 [%0], %1;" ::"l"(&scr->kvflag[idx * 8]), "r"(tag) : "memory");
                }
            }
            __syncwarp();
            mbar_wait(BAR(R_Q), 0);
            gather_issue(scr->o + (size_t)(2 * b) * 4096, true, tag, lane, SLOTA(4), SB + OFF_QX + 16384, BAR(F_O0));
            mbar_wait(BAR(R_O0), 0);
            gather_issue(scr->x2 + (size_t)(2 * b) * 4096, false, tag, lane, SLOTA(4), SB + OFF_QX + 16384, BAR(F_Y0));
            return;
        }
        if (hw == 2) {
            tag += 1;
            const int nh = b < 2 ? b : 2;
            mbar_wait(BAR(R_K), 0);
            if (nh < 2) {
                const uint32_t bytes = (2 - nh) * 2 * KVT;
#pragma unroll 1
                for (uint32_t o = lane * 16; o < bytes; o += 512) {
                    sts128(SLOTA(0) + o, 0, 0, 0, 0);
                    sts128(SLOTA(1) + o, 0, 0, 0, 0);
                }
                fence_async_smem();
                __syncwarp();
            }
            if (lane == 0) {
                mbar_expect_tx(BAR(F_HK), nh * 2 * KVT);
                mbar_expect_tx(BAR(F_HV), nh * 2 * KVT);
            }
            __syncwarp();
            {
                const int m = (lane >> 1) & 1, h = lane & 1;
                const int idx = ((b - 2 + h) * 8 + j) * 2 + m;
                bool todo = lane < 4 && h >= 2 - nh;
                int it = 0;
#pragma unroll 1
                while (__any_sync(0xFFFFFFFFu, todo) && ++it < SPIN_LIMIT) {
                    if (todo && ld_rlx32(&scr->kvflag[idx * 8]) == tag) {
                        bulk_g2s(SLOTA(0) + m * SLOT + h * 2 * KVT, scr->kv + (size_t)idx * 2 * KVT, 2 * KVT, BAR(F_HK) + 8 * m);
                        todo = false;
                    }
                }
            }
            mbar_wait(BAR(R_ATT), 0);
            gather_issue(scr->o + (size_t)(2 * b + 1) * 4096, true, tag, lane, SLOTA(0), SB + OFF_QX, BAR(F_O1));
            mbar_wait(BAR(R_O1), 0);
            gather_issue(scr->x2 + (size_t)(2 * b + 1) * 4096, false, tag, lane, SLOTA(0), SB + OFF_QX, BAR(F_Y1));
        } else {
            tag += 1;
            if (bid < 112) {
                const int col = 896 + bid * 16 + (lane & 1) * 8;
                const uint32_t slab = SB + OFF_QX, sil = SB + OFF_QX + 14336;
#pragma unroll
                for (int i = 0; i < 7; i++) {
                    const uint32_t cc = ((const uint32_t*)cvec)[lane + 32 * i];
                    sts32(sil + (lane + 32 * i) * 8, __float_as_uint(silu_bf(bf_lo(cc))));
                    sts32(sil + (lane + 32 * i) * 8 + 4, __float_as_uint(silu_bf(bf_hi(cc))));
                }
                mbar_wait(BAR(F_V0), 0);
                if (lane == 0) {
                    mbar_expect_tx(BAR(F_WM), 14336);
                    tma_2d(slab, &tm_m, 896 + bid * 16, 0, BAR(F_WM));
                    tma_2d(slab + 7168, &tm_m, 896 + bid * 16, 224, BAR(F_WM));
                }
                __syncwarp();
                mbar_wait(BAR(F_WM), 0);
                float a[8];
#pragma unroll
                for (int i = 0; i < 8; i++) a[i] = 0.f;
#pragma unroll 4
                for (int i = 0; i < 28; i++)
                    fma8(a, __uint_as_float(lds32(sil + ((lane >> 1) + 16 * i) * 4)), lds128(slab + i * 512 + lane * 16));
                {
                    bool up = lane & 16;
#pragma unroll
                    for (int i = 0; i < 4; i++) {
                        float keep = up ? a[i + 4] : a[i], send = up ? a[i] : a[i + 4];
                        a[i] = keep + __shfl_xor_sync(0xFFFFFFFFu, send, 16);
                    }
                    up = lane & 8;
#pragma unroll
                    for (int i = 0; i < 2; i++) {
                        float keep = up ? a[i + 2] : a[i], send = up ? a[i] : a[i + 2];
                        a[i] = keep + __shfl_xor_sync(0xFFFFFFFFu, send, 8);
                    }
#pragma unroll
                    for (int o = 2; o < 8; o <<= 1) {
                        a[0] += __shfl_xor_sync(0xFFFFFFFFu, a[0], o);
                        a[1] += __shfl_xor_sync(0xFFFFFFFFu, a[1], o);
                    }
                }
                if ((lane & 6) == 0) st_rlx64(&scr->mod[(col >> 1) + (lane >> 3)], pack2(a[0], a[1]), tag);
            }
            __syncwarp();
            if (lane == 0) mbar_arrive(BAR(R_WM));
#pragma unroll 1
            for (int h = 0; h < 2; h++) {
                uint2 mv[8];
                int it = 0;
                uint32_t bad;
#pragma unroll 1
                do {
                    bad = 0;
#pragma unroll
                    for (int i = 0; i < 7; i++) mv[i] = ld_rlx64(&scr->mod[672 + 224 * h + lane + 32 * i]);
                    mv[7] = ld_rlx64(&scr->mod[448 + 672 * h + 28 * j + (lane < 28 ? lane : 0)]);
#pragma unroll
                    for (int i = 0; i < 8; i++) bad |= mv[i].y ^ tag;
                } while (bad && ++it < SPIN_LIMIT);
#pragma unroll
                for (int i = 0; i < 7; i++)
                    sts32(SB + (h ? OFF_C2 : OFF_S2) + perm_off(lane + 32 * i), h ? hfma2(mv[i].x, 0x3F803F80u, 0x3F803F80u) : mv[i].x);
                if (lane < 28) sts32(SB + (h ? OFF_GB : OFF_GA) + lane * 4, mv[7].x);
            }
            __syncwarp();
            if (lane == 0) mbar_arrive(BAR(F_MOD2));
        }
    } else {
        const int w = wgi, t = tid & 127, warp = t >> 5, r = lane >> 2, q = lane & 3;
        const int tile = 2 * b + w;
        const int row0 = 64 * tile + 16 * warp + r;
        const uint32_t jo = (j & 1) * 16;

        const int mt = bid < 112 ? bid : 111;
        const int mcg = mt % 28, mrs = mt / 28;
        const int mrow = 112 * mrs + (tid >> 2), mrow1 = tid < 192 ? mrow + 64 : mrow;
        const uint4 wm0 = ldg128(wmod + (size_t)mrow * 2688 + mcg * 32 + (tid & 3) * 8);
        const uint4 wm1 = ldg128(wmod + (size_t)mrow1 * 2688 + mcg * 32 + (tid & 3) * 8);
        unsigned short cv0, cv1;
        asm volatile("ld.global.nc.u16 %0, [%1];" : "=h"(cv0) : "l"(cvec + mrow));
        asm volatile("ld.global.nc.u16 %0, [%1];" : "=h"(cv1) : "l"(cvec + mrow1));
        uint32_t tag = ld_rlx32(&scr->epoch[bid * 32 + lane]);
        TS(12);
        tag += 1;
        if (bid < 112) {
            float a[8];
#pragma unroll
            for (int i = 0; i < 8; i++) a[i] = 0.f;
            fma8(a, silu_bf(bf_lo(cv0)), wm0);
            fma8(a, tid < 192 ? silu_bf(bf_lo(cv1)) : 0.f, wm1);
            const float v = reduce8(a, lane);
            sts32(SB + OFF_RED + ((tid >> 5) * 32 + 8 * (lane & 3) + (lane >> 2)) * 4, __float_as_uint(v));
            if (tid < 32) {
                bar_sync(1, 256);
                if (lane < 8) {
                    float4 acc = make_float4(0.f, 0.f, 0.f, 0.f);
#pragma unroll
                    for (int k = 0; k < 8; k++) {
                        const uint4 u = lds128(SB + OFF_RED + k * 128 + lane * 16);
                        acc.x += __uint_as_float(u.x); acc.y += __uint_as_float(u.y);
                        acc.z += __uint_as_float(u.z); acc.w += __uint_as_float(u.w);
                    }
                    st_rlx128(&scr->modp[mrs * 224 + mcg * 8 + lane], (__float_as_uint(acc.x) & ~15u) | (tag & 15u),
                              (__float_as_uint(acc.y) & ~15u) | ((tag >> 4) & 15u), (__float_as_uint(acc.z) & ~15u) | ((tag >> 8) & 15u),
                              (__float_as_uint(acc.w) & ~15u) | ((tag >> 12) & 15u));
                }
                __syncwarp();
            } else {
                bar_arrive(1, 256);
            }
        }
        TS(13);
        asm volatile("setmaxnreg.inc.sync.aligned.u32 232;");
        bar_sync(2, 384);
        uint32_t rn1[4];
        uint32_t af[28][4];
        {
            const int xr_ = 64 * w + 16 * warp + (lane & 7) + 8 * ((lane >> 3) & 1);
            const uint32_t xa = SLOTA(3) + xr_ * 128;
            const uint32_t hi = lane >> 4, sw = lane & 7;
            float c1[2][4], c2[2][4], c3[2][4];
#pragma unroll
            for (int i = 0; i < 4; i++) c1[0][i] = c1[1][i] = c2[0][i] = c2[1][i] = c3[0][i] = c3[1][i] = 0.f;
#pragma unroll
            for (int g = 0; g < 2; g++) {
                const int s0 = 16 * g, s1 = g ? 28 : 16;
                mbar_wait(BAR(F_X0 + g), 0);
#pragma unroll
                for (int s = s0; s < s1; s++) ldsm4(af[s], xa + (s >> 2) * 16384 + (((2 * (s & 3) + hi) ^ sw) << 4));
                if (g == 1) {
                    __syncwarp();
                    if (lane == 0) mbar_arrive(BAR(R_X));
                }
#pragma unroll
                for (int s = s0; s < s1; s++) {
                    hmma(c1[s & 1], af[s], af[s][0], af[s][2]);
                    hmma(c2[s & 1], af[s], af[s][1], af[s][3]);
                    hmma(c3[s & 1], af[s], 0x3F803F80u, 0x3F803F80u);
                }
            }
            TS(14);
            const int src = (lane & ~3) | (r >> 1);
            const float qa = __shfl_sync(0xFFFFFFFFu, (r & 1) ? c1[0][1] + c1[1][1] : c1[0][0] + c1[1][0], src);
            const float qb = __shfl_sync(0xFFFFFFFFu, (r & 1) ? c2[0][3] + c2[1][3] : c2[0][2] + c2[1][2], src);
            const float ma = (c3[0][0] + c3[1][0]) * (1.0f / DM), mb = (c3[0][2] + c3[1][2]) * (1.0f / DM);
            const float rsa = bf_lo(pack2(rsqrtf(fmaxf(fmaf(-ma, ma, qa * (1.0f / DM)), 0.f) + 1e-5f), 0.f));
            const float rsb = bf_lo(pack2(rsqrtf(fmaxf(fmaf(-mb, mb, qb * (1.0f / DM)), 0.f) + 1e-5f), 0.f));
            rn1[0] = pack2(rsa, rsa); rn1[1] = pack2(-ma * rsa, -ma * rsa);
            rn1[2] = pack2(rsb, rsb); rn1[3] = pack2(-mb * rsb, -mb * rsb);
        }
        {
            uint4 mp[4];
            const int mi = tid < 224 ? tid : 0;
#pragma unroll
            for (int k = 0; k < 4; k++) mp[k] = ld_rlx128(&scr->modp[k * 224 + mi]);
#pragma unroll
            for (int s = 0; s < 28; s++) {
                af[s][0] = hfma2(af[s][0], rn1[0], rn1[1]);
                af[s][1] = hfma2(af[s][1], rn1[2], rn1[3]);
                af[s][2] = hfma2(af[s][2], rn1[0], rn1[1]);
                af[s][3] = hfma2(af[s][3], rn1[2], rn1[3]);
                pin(af[s]);
            }
            int it = 0;
            uint32_t bad;
#pragma unroll 1
            while (true) {
                bad = 0;
#pragma unroll
                for (int k = 0; k < 4; k++)
                    bad |= (((mp[k].x & 15u) | ((mp[k].y & 15u) << 4) | ((mp[k].z & 15u) << 8) | ((mp[k].w & 15u) << 12)) ^ tag) & 0xFFFFu;
                if (!bad || ++it > SPIN_LIMIT) break;
#pragma unroll
                for (int k = 0; k < 4; k++) mp[k] = ld_rlx128(&scr->modp[k * 224 + mi]);
            }
            if (tid < 224) {
                float f[4] = {0.f, 0.f, 0.f, 0.f};
#pragma unroll
                for (int k = 0; k < 4; k++) {
                    f[0] += __uint_as_float(mp[k].x & ~15u); f[1] += __uint_as_float(mp[k].y & ~15u);
                    f[2] += __uint_as_float(mp[k].z & ~15u); f[3] += __uint_as_float(mp[k].w & ~15u);
                }
                uint32_t p0 = pack2(f[0], f[1]), p1 = pack2(f[2], f[3]);
                const bool isc = tid >= 112;
                if (isc) { p0 = hfma2(p0, 0x3F803F80u, 0x3F803F80u); p1 = hfma2(p1, 0x3F803F80u, 0x3F803F80u); }
                const int pp = 2 * (isc ? tid - 112 : tid);
                const uint32_t tb = SB + (isc ? OFF_C1 : OFF_S1);
                sts32(tb + perm_off(pp), p0);
                sts32(tb + perm_off(pp + 1), p1);
            }
        }
        bar_sync(1, 256);
        TS(2);

        float accK[28], accV[28], accQ[28];
#pragma unroll
        for (int g = 0; g < 4; g++) {
            const int s0 = 14 * (g >> 1) + 8 * (g & 1), s1 = (g & 1) ? s0 + 6 : s0 + 8;
#pragma unroll
            for (int s = s0; s < s1; s += 2) {
                const uint4 c4 = lds128(SB + OFF_C1 + (s >> 1) * 64 + q * 16), s4 = lds128(SB + OFF_S1 + (s >> 1) * 64 + q * 16);
                af[s][0] = hfma2(af[s][0], c4.x, s4.x);
                af[s][1] = hfma2(af[s][1], c4.x, s4.x);
                af[s][2] = hfma2(af[s][2], c4.y, s4.y);
                af[s][3] = hfma2(af[s][3], c4.y, s4.y);
                af[s + 1][0] = hfma2(af[s + 1][0], c4.z, s4.z);
                af[s + 1][1] = hfma2(af[s + 1][1], c4.z, s4.z);
                af[s + 1][2] = hfma2(af[s + 1][2], c4.w, s4.w);
                af[s + 1][3] = hfma2(af[s + 1][3], c4.w, s4.w);
                pin(af[s]);
                pin(af[s + 1]);
            }
            if ((g & 1) == 0) mbar_wait(BAR(F_K0 + (g >> 1)), 0);
            WG_FENCE();
#pragma unroll
            for (int s = s0; s < s1; s++)
                wgmma_n56_t1(accK, af[s], mk_desc(SLOTA(s / 14) + (s % 14) * 2048 + jo, 0, 1024, 1), s != 0);
        }
        WG_COMMIT();
        mbar_wait(BAR(F_V0), 0);
        WG_FENCE();
#pragma unroll
        for (int s = 0; s < 7; s++) wgmma_n56_t1(accV, af[s], mk_desc(SLOTA(2) + s * 2048 + jo, 0, 1024, 1), s != 0);
        WG_COMMIT();
        mbar_wait(BAR(R_X), 0);
        WG_WAIT(1);
        pin(accK);
        if (lane == 0) mbar_arrive(BAR(R_K));
        store_kv(SLOTA(6) + w * KVT, accK, warp, lane);
        fence_async_smem();
        __syncwarp();
        if (lane == 0) mbar_arrive(BAR(R_KST));
        WG_FENCE();
#pragma unroll
        for (int s = 7; s < 14; s++) wgmma_n56_t1(accV, af[s], mk_desc(SLOTA(2) + s * 2048 + jo, 0, 1024, 1), 1);
        mbar_wait(BAR(F_V1), 0);
        WG_FENCE();
#pragma unroll
        for (int s = 0; s < 14; s++) wgmma_n56_t1(accV, af[14 + s], mk_desc(SLOTA(3) + s * 2048 + jo, 0, 1024, 1), 1);
        WG_COMMIT();
        mbar_wait(BAR(F_Q0), 0);
        WG_FENCE();
#pragma unroll
        for (int s = 0; s < 7; s++) wgmma_n56_t1(accQ, af[s], mk_desc(SLOTA(4) + s * 2048 + jo, 0, 1024, 1), s != 0);
        WG_COMMIT();
        WG_WAIT(1);
        pin(accV);
        if (lane == 0) mbar_arrive(BAR(R_V));
        store_kv(SLOTA(6) + 2 * KVT + w * KVT, accV, warp, lane);
        fence_async_smem();
        __syncwarp();
        if (lane == 0) mbar_arrive(BAR(R_VST));
        WG_FENCE();
#pragma unroll
        for (int s = 7; s < 14; s++) wgmma_n56_t1(accQ, af[s], mk_desc(SLOTA(4) + s * 2048 + jo, 0, 1024, 1), 1);
        mbar_wait(BAR(F_Q1), 0);
        WG_FENCE();
#pragma unroll
        for (int s = 0; s < 14; s++) wgmma_n56_t1(accQ, af[14 + s], mk_desc(SLOTA(5) + s * 2048 + jo, 0, 1024, 1), 1);
        WG_COMMIT();
        WG_WAIT(0);
        pin(accQ);
        if (lane == 0) mbar_arrive(BAR(R_Q));
        mbar_wait(BAR(R_WM), 0);
        {
            uint32_t p[14];
#pragma unroll
            for (int i = 0; i < 14; i++) p[i] = pack2(accQ[2 * i], accQ[2 * i + 1]);
            const uint32_t qa = SB + OFF_QX + w * 8192 + t * 16;
            const bool lo = q < 2;
            sts128(qa, p[0], p[1], p[2], p[3]);
            sts128(qa + 2048, p[4], p[5], lo ? p[6] : 0u, lo ? p[7] : 0u);
            sts128(qa + 4096, lo ? 0u : p[6], lo ? 0u : p[7], p[8], p[9]);
            sts128(qa + 6144, p[10], p[11], p[12], p[13]);
        }
        bar_sync(1, 256);
        TS(3);

        const float SC = 0.18898223650461362f * 1.4426950408889634f;
#pragma unroll 1
        for (int u = 0; u < 2; u++) {
            uint32_t qf[2][4];
            {
                const uint32_t qa = SB + OFF_QX + u * 8192 + w * 4096 + t * 16;
                const uint4 q0 = lds128(qa), q1 = lds128(qa + 2048);
                qf[0][0] = q0.x; qf[0][1] = q0.y; qf[0][2] = q0.z; qf[0][3] = q0.w;
                qf[1][0] = q1.x; qf[1][1] = q1.y; qf[1][2] = q1.z; qf[1][3] = q1.w;
            }
            const int first = 2 * b + u - 4;
            uint32_t ka[5];
#pragma unroll
            for (int kt = 0; kt < 5; kt++) {
                const int lt = u + kt;
                ka[kt] = (lt < 4 ? SLOTA(0) + lt * KVT : SLOTA(6) + (lt - 4) * KVT) + w * 3072;
            }
            float s[5][32];
            {
                const float init = first >= 0 ? 0.f : -INFINITY;
#pragma unroll
                for (int i = 0; i < 32; i++) s[0][i] = init;
            }
            pin(s[0]);
            pin(qf[0]);
            pin(qf[1]);
            WG_FENCE();
            wgmma_n64_t0(s[4], qf[0], mk_desc(ka[4], 1024, 128, 0), 0);
            wgmma_n64_t0(s[4], qf[1], mk_desc(ka[4] + 2048, 1024, 128, 0), 1);
            mbar_wait(BAR(F_HK), 0);
            WG_FENCE();
            wgmma_n64_t0(s[0], qf[0], mk_desc(ka[0], 1024, 128, 0), 1);
            wgmma_n64_t0(s[0], qf[1], mk_desc(ka[0] + 2048, 1024, 128, 0), 1);
            WG_COMMIT();
#pragma unroll
            for (int kt = 3; kt >= 1; kt--) {
                wgmma_n64_t0(s[kt], qf[0], mk_desc(ka[kt], 1024, 128, 0), 0);
                wgmma_n64_t0(s[kt], qf[1], mk_desc(ka[kt] + 2048, 1024, 128, 0), 1);
            }
            WG_COMMIT();
            WG_WAIT(1);
            pin(s[0]);
            pin(s[4]);
            const int d0 = 16 * warp + r - 2 * q;
            float mx[2] = {-INFINITY, -INFINITY};
#pragma unroll
            for (int i = 0; i < 8; i++)
#pragma unroll
                for (int rh = 0; rh < 2; rh++)
#pragma unroll
                    for (int e = 0; e < 2; e++) {
                        s[4][4 * i + 2 * rh + e] = (8 * i + e - 8 * rh <= d0) ? s[4][4 * i + 2 * rh + e] : s[0][4 * i + 2 * rh + e];
                        mx[rh] = fmaxf(mx[rh], s[4][4 * i + 2 * rh + e]);
                    }
            pin(s[4]);
            WG_WAIT(0);
#pragma unroll
            for (int kt = 1; kt < 4; kt++) pin(s[kt]);
#pragma unroll
            for (int kt = 1; kt < 4; kt++) {
                float tm[2] = {-INFINITY, -INFINITY};
#pragma unroll
                for (int i = 0; i < 8; i++) {
                    tm[0] = fmaxf(tm[0], fmaxf(s[kt][4 * i], s[kt][4 * i + 1]));
                    tm[1] = fmaxf(tm[1], fmaxf(s[kt][4 * i + 2], s[kt][4 * i + 3]));
                }
                if (first + kt >= 0) { mx[0] = fmaxf(mx[0], tm[0]); mx[1] = fmaxf(mx[1], tm[1]); }
            }
            mx[0] = -quad_max(mx[0]) * SC;
            mx[1] = -quad_max(mx[1]) * SC;
            asm volatile("" : "+f"(mx[0]), "+f"(mx[1])::"memory");
            if (w | u) mbar_wait(BAR(T_TOK) + 8 * (4 * w + warp), w & u);
            float o[16], ls[2] = {0.f, 0.f};
            uint32_t pf[5][4][4];
#pragma unroll
            for (int kk = 0; kk < 4; kk++) {
                const int kt = kk == 0 ? 4 : 4 - kk;
                const bool ok = kt == 4 || first + kt >= 0;
                const float n0 = ok ? mx[0] : -INFINITY, n1 = ok ? mx[1] : -INFINITY;
#pragma unroll
                for (int i = 0; i < 8; i++) {
                    const float p0 = ex2f(fmaf(s[kt][4 * i], SC, n0)), p1 = ex2f(fmaf(s[kt][4 * i + 1], SC, n0));
                    const float p2 = ex2f(fmaf(s[kt][4 * i + 2], SC, n1)), p3 = ex2f(fmaf(s[kt][4 * i + 3], SC, n1));
                    ls[0] += p0 + p1;
                    ls[1] += p2 + p3;
                    pf[kt][i >> 1][2 * (i & 1)] = pack2(p0, p1);
                    pf[kt][i >> 1][2 * (i & 1) + 1] = pack2(p2, p3);
                }
                if (kt == 4) {
#pragma unroll
                    for (int i = 0; i < 8; i++)
#pragma unroll
                        for (int rh = 0; rh < 2; rh++) {
                            const int sh = max(16 * (d0 + 8 * rh - 8 * i + 1), 0);
                            uint32_t nm;
                            asm("shl.b32 %0, %1, %2;" : "=r"(nm) : "r"(0xFFFFFFFFu), "r"(sh));
                            const uint32_t pv = pf[4][i >> 1][2 * (i & 1) + rh];
                            pf[0][i >> 1][2 * (i & 1) + rh] = pv & nm;
                            pf[4][i >> 1][2 * (i & 1) + rh] = pv & ~nm;
                        }
                }
#pragma unroll
                for (int ks = 0; ks < 4; ks++) pin(pf[kt][ks]);
                if (kt == 4) {
#pragma unroll
                    for (int ks = 0; ks < 4; ks++) pin(pf[0][ks]);
                    mbar_wait(BAR(F_HV), 0);
                }
                if (kk == TOKEN_KK && lane == 0) mbar_arrive(BAR(T_TOK) + 8 * (4 * (1 - w) + warp));
                WG_FENCE();
                const uint32_t voff = (u + kt < 4) ? SLOT : 2 * KVT;
#pragma unroll
                for (int ks = 0; ks < 4; ks++)
                    wgmma_n32_t1(o, pf[kt][ks], mk_desc(ka[kt] + voff + ks * 256, 128, 1024, 0), (kk | ks) != 0);
                if (kt == 4) {
#pragma unroll
                    for (int ks = 0; ks < 4; ks++) wgmma_n32_t1(o, pf[0][ks], mk_desc(ka[0] + SLOT + ks * 256, 128, 1024, 0), 1);
                }
                WG_COMMIT();
            }
            const float il0 = __frcp_rn(quad_sum(ls[0])), il1 = __frcp_rn(quad_sum(ls[1]));
            WG_WAIT(0);
            pin(o);
            uint32_t pk[8];
#pragma unroll
            for (int i = 0; i < 4; i++) {
                pk[2 * i] = pack2(o[4 * i] * il0, o[4 * i + 1] * il0);
                pk[2 * i + 1] = pack2(o[4 * i + 2] * il1, o[4 * i + 3] * il1);
            }
            {
                uint32_t f[6];
#pragma unroll
                for (int i = 0; i < 4; i++) f[i] = w ? pk[i + 4] : pk[i];
                f[4] = w ? pk[2] : pk[4];
                f[5] = w ? pk[3] : pk[5];
                const uint32_t part0 = w ? pk[0] : pk[6], part1 = w ? pk[1] : pk[7];
                const uint32_t got = __shfl_xor_sync(0xFFFFFFFFu, w ? part0 : part1, 2);
                const bool lo = q < 2;
                const uint32_t ex = (lo == (w == 0)) ? (lo ? part0 : part1) : got;
                uint4* dst = scr->o + (((2 * b + u) * 8 + j) * 4 + 2 * w) * 128 + t;
                st_rlx128(dst, f[0], f[1], f[2], prmt(f[3], tag, 0x1054));
                st_rlx128(dst + 128, f[4], f[5], ex, prmt(f[3], tag, 0x3254));
            }
            TS(4 + u);
        }
        if (lane == 0) mbar_arrive(BAR(R_ATT));

        const uint32_t land = (w ? SLOTA(0) : SLOTA(4)) + t * 16, land_x = SB + OFF_QX + (w ? 0 : 16384) + t * 16;
        uint32_t xr[14];
#pragma unroll
        for (int i = 0; i < 7; i++) {
            xr[2 * i] = *(const uint32_t*)(x + (size_t)row0 * DM + 56 * j + 8 * i + 2 * q);
            xr[2 * i + 1] = *(const uint32_t*)(x + (size_t)(row0 + 8) * DM + 56 * j + 8 * i + 2 * q);
        }
        {
            uint4 v[8][4];
            mbar_wait(BAR(F_O0) + 8 * w, 0);
            if (__builtin_expect(landed_read(v, land, land_x, tag), 0)) {
                int it = 0;
#pragma unroll 1
                while (gather_try(v, scr->o + (size_t)tile * 4096 + t, tag) && ++it < SPIN_LIMIT) {}
            }
            if (lane == 0) mbar_arrive(BAR(R_O0) + 8 * w);
            const bool lo = q < 2;
#pragma unroll
            for (int s = 0; s < 8; s++) {
                const int k0 = 7 * (s >> 1) + 3 * (s & 1), k6 = 7 * (s >> 1) + 6;
                const uint32_t e0 = v[s][1].z, e1 = v[s][3].z;
                const uint32_t got = __shfl_xor_sync(0xFFFFFFFFu, lo ? e1 : e0, 2);
                af[k0][0] = v[s][0].x; af[k0][1] = v[s][0].y; af[k0][2] = v[s][0].z;
                af[k0][3] = prmt(v[s][0].w, v[s][1].w, 0x7632);
                af[k0 + 1][0] = v[s][1].x; af[k0 + 1][1] = v[s][1].y;
                af[k0 + 1][2] = lo ? e0 : got; af[k0 + 1][3] = lo ? got : e1;
                af[k0 + 2][0] = v[s][2].x; af[k0 + 2][1] = v[s][2].y; af[k0 + 2][2] = v[s][2].z;
                af[k0 + 2][3] = prmt(v[s][2].w, v[s][3].w, 0x7632);
                af[k6][2 * (s & 1)] = v[s][3].x; af[k6][2 * (s & 1) + 1] = v[s][3].y;
            }
        }
        TS(6);
        float accO[28];
#pragma unroll
        for (int s = 0; s < 28; s++) pin(af[s]);
#pragma unroll
        for (int hf = 0; hf < 2; hf++) {
            mbar_wait(BAR(F_WO0 + hf), 0);
            WG_FENCE();
#pragma unroll
            for (int s = 0; s < 14; s++)
                wgmma_n56_t1(accO, af[14 * hf + s],
                             mk_desc(SLOTA(2 + hf) + ((s / 7) * 14 + kstep_group<4>(s % 7)) * 1024 + jo, 0, 1024 * kstep_gap(s % 7), 1),
                             (hf | s) != 0);
        }
        WG_COMMIT();
        mbar_wait(BAR(F_MOD2), 0);
        WG_WAIT(0);
        pin(accO);
        if (lane == 0) mbar_arrive(BAR(R_WO));
        {
            float s0 = 0.f, s1 = 0.f;
#pragma unroll
            for (int i = 0; i < 7; i++) {
                const uint32_t g = lds32(SB + OFF_GA + (4 * i + q) * 4);
                accO[4 * i] = fmaf(bf_lo(g), accO[4 * i], bf_lo(xr[2 * i]));
                accO[4 * i + 1] = fmaf(bf_hi(g), accO[4 * i + 1], bf_hi(xr[2 * i]));
                accO[4 * i + 2] = fmaf(bf_lo(g), accO[4 * i + 2], bf_lo(xr[2 * i + 1]));
                accO[4 * i + 3] = fmaf(bf_hi(g), accO[4 * i + 3], bf_hi(xr[2 * i + 1]));
                s0 += accO[4 * i] + accO[4 * i + 1];
                s1 += accO[4 * i + 2] + accO[4 * i + 3];
            }
            uint32_t p[14];
#pragma unroll
            for (int i = 0; i < 14; i++) p[i] = pack2(accO[2 * i], accO[2 * i + 1]);
            publish14(scr->x2 + ((size_t)tile * 8 + j) * 512 + t, p, tag);
            s0 = quad_sum(s0) * (1.0f / 56);
            s1 = quad_sum(s1) * (1.0f / 56);
            float m0 = 0.f, m1 = 0.f;
#pragma unroll
            for (int i = 0; i < 7; i++) {
                float d;
                d = accO[4 * i] - s0; m0 = fmaf(d, d, m0);
                d = accO[4 * i + 1] - s0; m0 = fmaf(d, d, m0);
                d = accO[4 * i + 2] - s1; m1 = fmaf(d, d, m1);
                d = accO[4 * i + 3] - s1; m1 = fmaf(d, d, m1);
            }
            m0 = quad_sum(m0);
            m1 = quad_sum(m1);
            if (q < 2)
                st_rlx128(scr->st2 + ((size_t)tile * 8 + j) * 64 + 16 * warp + r + 8 * q, __float_as_uint(q ? s1 : s0),
                          __float_as_uint(q ? m1 : m0), tag, 0);
        }
        TS(7);

        {
            uint32_t rn[2][2];
            {
                uint4 st[4];
                const uint4* sp = scr->st2 + ((size_t)tile * 8 + 2 * q) * 64 + 16 * warp + r;
                int it = 0;
#pragma unroll 1
                while (true) {
                    st[0] = ld_rlx128(sp); st[1] = ld_rlx128(sp + 64); st[2] = ld_rlx128(sp + 8); st[3] = ld_rlx128(sp + 72);
                    const bool bad = st[0].z != tag || st[1].z != tag || st[2].z != tag || st[3].z != tag;
                    if (!__any_sync(0xFFFFFFFFu, bad)) break;
                    if (++it > SPIN_LIMIT) break;
                }
#pragma unroll
                for (int rh = 0; rh < 2; rh++) {
                    const float ma = __uint_as_float(st[2 * rh].x), mb = __uint_as_float(st[2 * rh + 1].x);
                    const float mean = quad_sum(ma + mb) * 0.125f;
                    const float da = ma - mean, db = mb - mean;
                    const float m2 = quad_sum(__uint_as_float(st[2 * rh].y) + __uint_as_float(st[2 * rh + 1].y) + 56.f * (da * da + db * db));
                    const float rs = bf_lo(pack2(rsqrtf(m2 * (1.0f / DM) + 1e-5f), 0.f));
                    rn[rh][0] = pack2(rs, rs);
                    rn[rh][1] = pack2(-mean * rs, -mean * rs);
                }
            }
            TS(15);
            uint4 v[8][4];
            mbar_wait(BAR(F_Y0) + 8 * w, 0);
            if (__builtin_expect(landed_read(v, land, land_x, tag), 0)) {
                int it = 0;
#pragma unroll 1
                while (gather_try(v, scr->x2 + (size_t)tile * 4096 + t, tag) && ++it < SPIN_LIMIT) {}
            }
            if (lane == 0) mbar_arrive(BAR(R_Y0) + 8 * w);
            uint32_t cw[56], sw[56];
#pragma unroll
            for (int s = 0; s < 8; s++) {
                uint32_t rr[14];
                unpack14(v[s], rr);
#pragma unroll
                for (int i = 0; i < 7; i++) {
                    const int blk = 7 * s + i;
                    if ((blk & 3) == 0) {
                        const uint4 c4 = lds128(SB + OFF_C2 + (blk >> 2) * 64 + q * 16), s4 = lds128(SB + OFF_S2 + (blk >> 2) * 64 + q * 16);
                        cw[blk] = c4.x; cw[blk + 1] = c4.y; cw[blk + 2] = c4.z; cw[blk + 3] = c4.w;
                        sw[blk] = s4.x; sw[blk + 1] = s4.y; sw[blk + 2] = s4.z; sw[blk + 3] = s4.w;
                    }
                    const int ks = 7 * (s >> 1) + (i == 6 ? 6 : 3 * (s & 1) + (i >> 1));
                    const int hi = i == 6 ? (s & 1) : (i & 1);
                    af[ks][2 * hi] = hfma2(hfma2(rr[2 * i], rn[0][0], rn[0][1]), cw[blk], sw[blk]);
                    af[ks][2 * hi + 1] = hfma2(hfma2(rr[2 * i + 1], rn[1][0], rn[1][1]), cw[blk], sw[blk]);
                }
            }
        }
#pragma unroll
        for (int s = 0; s < 28; s++) pin(af[s]);
        TS(8);
        uint32_t hh[14][4];
        const uint32_t hs = SB + OFF_QX + (w ? 0 : 12288) + t * 16;
        {
            float acc[32];
#pragma unroll
            for (int st = 0; st < 2; st++) {
                const int n = N_GU3 + st;
                mbar_wait(BAR(F_RING + n % NSLOT), (n / NSLOT) & 1);
                WG_FENCE();
#pragma unroll
                for (int s = 0; s < 14; s++)
                    wgmma_n64_t1(acc, af[14 * st + s],
                                 mk_desc(SLOTA(ring_slot(n % NSLOT)) + ((s / 7) * 14 + kstep_group<6>(s % 7)) * 512, SLOT / 2,
                                         512 * kstep_gap(s % 7), 2),
                                 (st | s) != 0);
                WG_COMMIT();
                if (st > 0) {
                    WG_WAIT(1);
                    if (lane == 0) mbar_arrive(BAR(E_RING + (n - 1) % NSLOT));
                }
            }
            WG_WAIT(0);
            pin(acc);
            if (lane == 0) mbar_arrive(BAR(E_RING + (N_GU3 + 1) % NSLOT));
            uint32_t hp[8];
#pragma unroll
            for (int i = 0; i < 8; i++) hp[i] = pack2(fmaxf(acc[2 * i], 0.f) * acc[16 + 2 * i], fmaxf(acc[2 * i + 1], 0.f) * acc[17 + 2 * i]);
            sts128(hs + 4 * 2048, hp[0], hp[1], hp[2], hp[3]);
            sts128(hs + 5 * 2048, hp[4], hp[5], hp[6], hp[7]);
        }
#pragma unroll
        for (int p = 0; p < 3; p++) {
            float acc[64];
#pragma unroll
            for (int st = 0; st < 4; st++) {
                const int n = N_GU + 4 * p + st;
                mbar_wait(BAR(F_RING + n % NSLOT), (n / NSLOT) & 1);
                WG_FENCE();
#pragma unroll
                for (int s = 0; s < 7; s++)
                    wgmma_n128_t1(acc, af[7 * st + s],
                                  mk_desc(SLOTA(ring_slot(n % NSLOT)) + kstep_group<6>(s) * 1024, SLOT / 2, 1024 * kstep_gap(s), 1),
                                  (st | s) != 0);
                WG_COMMIT();
                if (st > 0) {
                    WG_WAIT(1);
                    if (lane == 0) mbar_arrive(BAR(E_RING + (n - 1) % NSLOT));
                }
            }
            WG_WAIT(0);
            pin(acc);
            if (lane == 0) mbar_arrive(BAR(E_RING + (N_GU + 4 * p + 3) % NSLOT));
#pragma unroll
            for (int i = 0; i < 16; i++)
                hh[4 * p + (i >> 2)][i & 3] = pack2(fmaxf(acc[2 * i], 0.f) * acc[32 + 2 * i], fmaxf(acc[2 * i + 1], 0.f) * acc[33 + 2 * i]);
            if (p == 0) {
#pragma unroll
                for (int k = 0; k < 4; k++) sts128(hs + k * 2048, hh[k][0], hh[k][1], hh[k][2], hh[k][3]);
            }
        }
#pragma unroll
        for (int k = 0; k < 6; k++) {
            const uint4 hv = lds128(hs + k * 2048);
            const int ks = k < 4 ? k : k + 8;
            hh[ks][0] = hv.x; hh[ks][1] = hv.y; hh[ks][2] = hv.z; hh[ks][3] = hv.w;
        }
#pragma unroll
        for (int s = 0; s < 14; s++) pin(hh[s]);
        TS(9);

        const uint32_t dbig = (j & 1) * 4096, dsmall = (j & 1) ? (uint32_t)-24576 : 0u;
        float accD[2][28], sum[28];
#pragma unroll
        for (int i = 0; i < 28; i++) sum[i] = 0.f;
        uint4 pv[4];
        const uint4* pin_base = scr->part + ((size_t)tile * 8 + j) * 4096 + t;
        uint4* pout_base = scr->part + (size_t)tile * 8 * 4096 + j * 512 + t;
        auto load_part = [&](int ps) {
            const uint4* src = pin_base + ((j + 7 - ps) & 7) * 512;
#pragma unroll
            for (int k = 0; k < 4; k++) pv[k] = ld_rlx128(src + k * 128);
        };
        auto add_part = [&](int ps) {
            int it = 0;
#pragma unroll 1
            while (__builtin_expect(__any_sync(0xFFFFFFFFu, tag_bad(pv, tag) != 0), 0)) {
                load_part(ps);
                if (++it > SPIN_LIMIT) break;
            }
            uint32_t rr[14];
            unpack14(pv, rr);
#pragma unroll
            for (int i = 0; i < 14; i++) {
                sum[2 * i] += bf_lo(rr[i]);
                sum[2 * i + 1] += bf_hi(rr[i]);
            }
        };
        auto issue_pass = [&](float (&acc)[28], int ps) {
            const int pos = ps == 7 ? 0 : ps;
            mbar_wait(BAR(F_RING) + 8 * pos, ps == 7);
            const uint32_t base = SB + ring_slot(pos) * SLOT + ((ps & 1) ? jo : 16 - jo);
            WG_FENCE();
#pragma unroll
            for (int s = 0; s < 14; s++) wgmma_n56_t1(acc, hh[s], mk_desc(base + s * 2048 + (s < 12 ? dbig : dsmall), 0, 1024, 1), s != 0);
            WG_COMMIT();
        };
        uint32_t pb[14];
        auto send_pass = [&](int ps) {
            publish14(pout_base + ((j + ps + 1) & 7) * 4096, pb, tag);
            if (ps >= 3) add_part(ps - 3);
            if (ps >= 2) load_part(ps - 2);
        };
#pragma unroll 1
        for (int pp = 0; pp < 8; pp += 2) {
            issue_pass(accD[0], pp);
            if (pp > 0) send_pass(pp - 1);
            issue_pass(accD[1], pp + 1);
            WG_WAIT(1);
            pin(accD[0]);
            if (pp == 0 && lane == 0) mbar_arrive(BAR(E_RING));
#pragma unroll
            for (int i = 0; i < 14; i++) pb[i] = pack2(accD[0][2 * i], accD[0][2 * i + 1]);
            send_pass(pp);
            if (pp == 6) break;
            WG_WAIT(0);
            pin(accD[1]);
#pragma unroll
            for (int i = 0; i < 14; i++) pb[i] = pack2(accD[1][2 * i], accD[1][2 * i + 1]);
        }
        TS(10);
        uint4 xv[4];
        {
            const uint4* src = scr->x2 + ((size_t)tile * 8 + j) * 512 + t;
#pragma unroll
            for (int k = 0; k < 4; k++) xv[k] = ld_rlx128(src + k * 128);
        }
#pragma unroll 1
        for (int ps = 4; ps < 7; ps++) {
            add_part(ps);
            if (ps < 6) load_part(ps + 1);
        }
        WG_WAIT(0);
        pin(accD[1]);
        {
            uint32_t rr[14];
            unpack14(xv, rr);
#pragma unroll
            for (int i = 0; i < 7; i++) {
                const uint32_t g = lds32(SB + OFF_GB + (4 * i + q) * 4);
                const float o0 = fmaf(bf_lo(g), sum[4 * i] + accD[1][4 * i], bf_lo(rr[2 * i]));
                const float o1 = fmaf(bf_hi(g), sum[4 * i + 1] + accD[1][4 * i + 1], bf_hi(rr[2 * i]));
                const float o2 = fmaf(bf_lo(g), sum[4 * i + 2] + accD[1][4 * i + 2], bf_lo(rr[2 * i + 1]));
                const float o3 = fmaf(bf_hi(g), sum[4 * i + 3] + accD[1][4 * i + 3], bf_hi(rr[2 * i + 1]));
                *(uint32_t*)(out + (size_t)row0 * DM + 56 * j + 8 * i + 2 * q) = pack2(o0, o1);
                *(uint32_t*)(out + (size_t)(row0 + 8) * DM + 56 * j + 8 * i + 2 * q) = pack2(o2, o3);
            }
        }
        if (tid < 32) scr->epoch[bid * 32 + lane] = tag;
        TS(11);
        TG(31);
    }
}

typedef CUresult (*EncodeFn)(CUtensorMap*, CUtensorMapDataType, cuuint32_t, void*, const cuuint64_t*, const cuuint64_t*,
                             const cuuint32_t*, const cuuint32_t*, CUtensorMapInterleave, CUtensorMapSwizzle,
                             CUtensorMapL2promotion, CUtensorMapFloatOOBfill);

void make_map_2d(EncodeFn enc, CUtensorMap* m, const void* ptr, uint64_t cols, uint64_t rows, uint32_t bc, uint32_t br,
                 CUtensorMapSwizzle swz) {
    cuuint64_t dims[2] = {cols, rows};
    cuuint64_t strides[1] = {cols * 2};
    cuuint32_t box[2] = {bc, br};
    cuuint32_t es[2] = {1, 1};
    enc(m, CU_TENSOR_MAP_DATA_TYPE_BFLOAT16, 2, const_cast<void*>(ptr), dims, strides, box, es, CU_TENSOR_MAP_INTERLEAVE_NONE, swz,
        CU_TENSOR_MAP_L2_PROMOTION_L2_128B, CU_TENSOR_MAP_FLOAT_OOB_FILL_NONE);
}

}

extern "C" void kernel_launch(void* const* d_in, const int* in_sizes, int n_in, void* d_out, int out_size) {
    (void)in_sizes; (void)n_in; (void)out_size;
    const __nv_bfloat16* x = (const __nv_bfloat16*)d_in[0];
    const __nv_bfloat16* wqkv = (const __nv_bfloat16*)d_in[1];
    const __nv_bfloat16* wo = (const __nv_bfloat16*)d_in[2];
    const __nv_bfloat16* wg = (const __nv_bfloat16*)d_in[4];
    const __nv_bfloat16* wu = (const __nv_bfloat16*)d_in[5];
    const __nv_bfloat16* wd = (const __nv_bfloat16*)d_in[6];
    const __nv_bfloat16* cv = (const __nv_bfloat16*)d_in[7];
    const __nv_bfloat16* wm = (const __nv_bfloat16*)d_in[8];

    void* fn = nullptr;
    cudaDriverEntryPointQueryResult qr;
    cudaGetDriverEntryPoint("cuTensorMapEncodeTiled", &fn, cudaEnableDefault, &qr);
    EncodeFn enc = (EncodeFn)fn;

    CUtensorMap tx, tq, two, tg, tu, tg3, tu3, td, tmm;
    make_map_2d(enc, &tmm, wm, 6 * DM, DM, 16, 224, CU_TENSOR_MAP_SWIZZLE_NONE);
    make_map_2d(enc, &tx, x, DM, SEQ, 64, 128, CU_TENSOR_MAP_SWIZZLE_128B);
    make_map_2d(enc, &tq, wqkv, 3 * DM, DM, 64, 224, CU_TENSOR_MAP_SWIZZLE_128B);
    make_map_2d(enc, &two, wo, DM, DM, 64, 224, CU_TENSOR_MAP_SWIZZLE_128B);
    make_map_2d(enc, &tg, wg, FF, DM, 64, 112, CU_TENSOR_MAP_SWIZZLE_128B);
    make_map_2d(enc, &tu, wu, FF, DM, 64, 112, CU_TENSOR_MAP_SWIZZLE_128B);
    make_map_2d(enc, &tg3, wg, FF, DM, 32, 224, CU_TENSOR_MAP_SWIZZLE_64B);
    make_map_2d(enc, &tu3, wu, FF, DM, 32, 224, CU_TENSOR_MAP_SWIZZLE_64B);
    make_map_2d(enc, &td, wd, DM, FF, 64, 224, CU_TENSOR_MAP_SWIZZLE_128B);

    cudaFuncSetAttribute(fused_block_kernel, cudaFuncAttributeMaxDynamicSharedMemorySize, SMEM_BYTES);
    void* scr = nullptr;
    cudaGetSymbolAddress(&scr, g_scr);
    fused_block_kernel<<<NCTA, NTHREADS, SMEM_BYTES>>>((Scratch*)scr, x, cv, wm, (__nv_bfloat16*)d_out, wqkv, wo, wg, wu, wd, tx, tq, two, tg,
                                                       tu, tg3, tu3, td, tmm);
}
```

```cpp
#include <cuda_runtime.h>
#include <cuda_bf16.h>
#include <cuda.h>
#include <stdint.h>

#define DBG_TIMING 0

namespace {

constexpr int SEQ = 2048, DM = 448, FF = 1792;
constexpr int NCTA = 128;
constexpr int NTHREADS = 384;
constexpr uint32_t SLOT = 28672;
constexpr int NSLOT = 7;
constexpr uint32_t KVT = 7168;
constexpr uint32_t OFF_QX = NSLOT * SLOT;
constexpr uint32_t OFF_C1 = OFF_QX + 24576;
constexpr uint32_t OFF_S1 = OFF_C1 + 896;
constexpr uint32_t OFF_C2 = OFF_S1 + 896;
constexpr uint32_t OFF_S2 = OFF_C2 + 896;
constexpr uint32_t OFF_GA = OFF_S2 + 896;
constexpr uint32_t OFF_GB = OFF_GA + 128;
constexpr uint32_t OFF_ONE = OFF_GB + 128;
constexpr uint32_t OFF_RED = OFF_ONE + 256;
constexpr uint32_t OFF_BAR = OFF_RED + 1024;
enum { F_X0, F_K0 = F_X0 + 2, F_K1, F_V0, F_V1, F_Q0, F_Q1, F_HK, F_HV, F_WO0, F_WO1, F_O0, F_O1, F_Y0, F_Y1, F_MOD2, F_WM, R_WM, T_TOK, F_RING = T_TOK + 8,
       N_ONE = F_RING + NSLOT,
       R_X = N_ONE, R_K, R_V, R_Q, R_ATT, R_WO, R_KST, R_VST, E_RING,
       N_EIGHT = E_RING + NSLOT,
       R_O0 = N_EIGHT, R_O1, R_Y0, R_Y1, N_BARS };
constexpr uint32_t SMEM_BYTES = OFF_BAR + 8 * N_BARS;
constexpr uint32_t SB = 0x400;
__host__ __device__ constexpr uint32_t BAR(int i) { return SB + OFF_BAR + 8 * i; }
__host__ __device__ constexpr uint32_t SLOTA(int i) { return SB + i * SLOT; }
__host__ __device__ constexpr int ring_slot(int i) { return i == 0 ? 6 : (i < 5 ? i + 1 : i - 5); }

constexpr int SPIN_LIMIT = 1 << 17;

struct Scratch {
    uint4 part[32 * 8 * 4 * 4 * 128];
    uint4 hx[32 * 8 * 18 * 128];
    uint4 o[32 * 8 * 4 * 128];
    uint4 x2[32 * 8 * 4 * 128];
    uint2 st2[32 * 8 * 64];
    uint8_t kv[16 * 8 * 2 * 2 * KVT];
    uint4 modp[4 * 224];
    uint2 mod[1344];
    uint32_t kvflag[16 * 8 * 2 * 8];
    uint32_t epoch[NCTA * 32];
};
__device__ __align__(1024) Scratch g_scr;

__device__ __forceinline__ uint32_t smem_u32(const void* p) { return (uint32_t)__cvta_generic_to_shared(p); }
__device__ __forceinline__ void mbar_init(uint32_t bar, uint32_t cnt) {
    asm volatile("mbarrier.init.shared::cta.b64 [%0], %1;" ::"r"(bar), "r"(cnt) : "memory");
}
__device__ __forceinline__ void mbar_arrive(uint32_t bar) {
    asm volatile("mbarrier.arrive.shared::cta.b64 _, [%0];" ::"r"(bar) : "memory");
}
__device__ __forceinline__ void mbar_expect_tx(uint32_t bar, uint32_t bytes) {
    asm volatile("mbarrier.arrive.expect_tx.shared::cta.b64 _, [%0], %1;" ::"r"(bar), "r"(bytes) : "memory");
}
__device__ __forceinline__ void mbar_wait(uint32_t bar, uint32_t parity) {
    uint32_t done;
    int it = 0;
#pragma unroll 1
    do {
        asm volatile("{\n.reg .pred p;\nmbarrier.try_wait.parity.shared::cta.b64 p, [%1], %2;\nselp.u32 %0, 1, 0, p;\n}\n"
                     : "=r"(done) : "r"(bar), "r"(parity) : "memory");
        if (++it > SPIN_LIMIT) break;
    } while (!done);
}
__device__ __forceinline__ void tma_2d(uint32_t dst, const CUtensorMap* m, int c0, int c1, uint32_t bar) {
    asm volatile("cp.async.bulk.tensor.2d.shared::cluster.global.mbarrier::complete_tx::bytes [%0], [%1, {%3, %4}], [%2];"
                 ::"r"(dst), "l"(m), "r"(bar), "r"(c0), "r"(c1) : "memory");
}
__device__ __forceinline__ void bulk_g2s(uint32_t dst, const void* src, uint32_t bytes, uint32_t bar) {
    asm volatile("cp.async.bulk.shared::cluster.global.mbarrier::complete_tx::bytes [%0], [%1], %2, [%3];"
                 ::"r"(dst), "l"(src), "r"(bytes), "r"(bar) : "memory");
}
__device__ __forceinline__ void bulk_s2g(void* dst, uint32_t src, uint32_t bytes) {
    asm volatile("cp.async.bulk.global.shared::cta.bulk_group [%0], [%1], %2;" ::"l"(dst), "r"(src), "r"(bytes) : "memory");
}
__device__ __forceinline__ void l2_prefetch(const void* src, uint32_t bytes) {
    asm volatile("cp.async.bulk.prefetch.L2.global [%0], %1;" ::"l"(src), "r"(bytes) : "memory");
}
__device__ __forceinline__ uint4 ld_rlx128(const uint4* p) {
    uint4 v;
    asm volatile("ld.relaxed.gpu.global.v4.u32 {%0,%1,%2,%3}, [%4];" : "=r"(v.x), "=r"(v.y), "=r"(v.z), "=r"(v.w) : "l"(p) : "memory");
    return v;
}
__device__ __forceinline__ void st_rlx128(uint4* p, uint32_t x, uint32_t y, uint32_t z, uint32_t w) {
    asm volatile("st.relaxed.gpu.global.v4.u32 [%0], {%1,%2,%3,%4};" ::"l"(p), "r"(x), "r"(y), "r"(z), "r"(w) : "memory");
}
__device__ __forceinline__ uint2 ld_rlx64(const uint2* p) {
    uint2 v;
    asm volatile("ld.relaxed.gpu.global.v2.u32 {%0,%1}, [%2];" : "=r"(v.x), "=r"(v.y) : "l"(p) : "memory");
    return v;
}
__device__ __forceinline__ void st_rlx64(uint2* p, uint32_t x, uint32_t y) {
    asm volatile("st.relaxed.gpu.global.v2.u32 [%0], {%1,%2};" ::"l"(p), "r"(x), "r"(y) : "memory");
}
__device__ __forceinline__ uint4 ldg128(const void* p) {
    uint4 v;
    asm volatile("ld.global.nc.L1::no_allocate.v4.u32 {%0,%1,%2,%3}, [%4];" : "=r"(v.x), "=r"(v.y), "=r"(v.z), "=r"(v.w) : "l"(p));
    return v;
}
__device__ __forceinline__ uint4 lds128(uint32_t a) {
    uint4 v;
    asm volatile("ld.shared.v4.u32 {%0,%1,%2,%3}, [%4];" : "=r"(v.x), "=r"(v.y), "=r"(v.z), "=r"(v.w) : "r"(a) : "memory");
    return v;
}
__device__ __forceinline__ uint2 lds64(uint32_t a) {
    uint2 v;
    asm volatile("ld.shared.v2.u32 {%0,%1}, [%2];" : "=r"(v.x), "=r"(v.y) : "r"(a) : "memory");
    return v;
}
__device__ __forceinline__ uint32_t lds32(uint32_t a) {
    uint32_t v;
    asm volatile("ld.shared.u32 %0, [%1];" : "=r"(v) : "r"(a) : "memory");
    return v;
}
__device__ __forceinline__ void sts128(uint32_t a, uint32_t x, uint32_t y, uint32_t z, uint32_t w) {
    asm volatile("st.shared.v4.u32 [%0], {%1,%2,%3,%4};" ::"r"(a), "r"(x), "r"(y), "r"(z), "r"(w) : "memory");
}
__device__ __forceinline__ void sts64(uint32_t a, uint32_t x, uint32_t y) {
    asm volatile("st.shared.v2.u32 [%0], {%1,%2};" ::"r"(a), "r"(x), "r"(y) : "memory");
}
__device__ __forceinline__ void sts32(uint32_t a, uint32_t x) { asm volatile("st.shared.u32 [%0], %1;" ::"r"(a), "r"(x) : "memory"); }
__device__ __forceinline__ void stsm4(uint32_t a, uint32_t r0, uint32_t r1, uint32_t r2, uint32_t r3) {
    asm volatile("stmatrix.sync.aligned.m8n8.x4.shared.b16 [%0], {%1,%2,%3,%4};" ::"r"(a), "r"(r0), "r"(r1), "r"(r2), "r"(r3) : "memory");
}
__device__ __forceinline__ void stsm2(uint32_t a, uint32_t r0, uint32_t r1) {
    asm volatile("stmatrix.sync.aligned.m8n8.x2.shared.b16 [%0], {%1,%2};" ::"r"(a), "r"(r0), "r"(r1) : "memory");
}
__device__ __forceinline__ void ldsm4(uint32_t (&r)[4], uint32_t a) {
    asm volatile("ldmatrix.sync.aligned.m8n8.x4.shared.b16 {%0,%1,%2,%3}, [%4];"
                 : "=r"(r[0]), "=r"(r[1]), "=r"(r[2]), "=r"(r[3]) : "r"(a) : "memory");
}
__device__ __forceinline__ void hmma(float (&c)[4], const uint32_t (&a)[4], uint32_t b0, uint32_t b1) {
    asm volatile("mma.sync.aligned.m16n8k16.row.col.f32.bf16.bf16.f32 {%0,%1,%2,%3}, {%4,%5,%6,%7}, {%8,%9}, {%0,%1,%2,%3};"
                 : "+f"(c[0]), "+f"(c[1]), "+f"(c[2]), "+f"(c[3])
                 : "r"(a[0]), "r"(a[1]), "r"(a[2]), "r"(a[3]), "r"(b0), "r"(b1));
}
__device__ __forceinline__ uint32_t ld_rlx32(const void* p) {
    uint32_t v;
    asm volatile("ld.relaxed.gpu.global.u32 %0, [%1];" : "=r"(v) : "l"(p) : "memory");
    return v;
}
__device__ __forceinline__ uint32_t pack2(float lo, float hi) {
    uint32_t r;
    asm("cvt.rn.bf16x2.f32 %0, %1, %2;" : "=r"(r) : "f"(hi), "f"(lo));
    return r;
}
__device__ __forceinline__ float bf_lo(uint32_t v) { return __uint_as_float(v << 16); }
__device__ __forceinline__ float bf_hi(uint32_t v) { return __uint_as_float(v & 0xFFFF0000u); }
__device__ __forceinline__ uint32_t hfma2(uint32_t a, uint32_t b, uint32_t c) {
    uint32_t r;
    asm("fma.rn.bf16x2 %0, %1, %2, %3;" : "=r"(r) : "r"(a), "r"(b), "r"(c));
    return r;
}
__device__ __forceinline__ uint32_t prmt(uint32_t a, uint32_t b, uint32_t sel) {
    uint32_t r;
    asm("prmt.b32 %0, %1, %2, %3;" : "=r"(r) : "r"(a), "r"(b), "r"(sel));
    return r;
}
__device__ __forceinline__ float ex2f(float x) {
    float r;
    asm("ex2.approx.ftz.f32 %0, %1;" : "=f"(r) : "f"(x));
    return r;
}
__device__ __forceinline__ uint32_t exp_pack(float a, float b, float sc, float n) {
    return pack2(ex2f(fmaf(a, sc, n)), ex2f(fmaf(b, sc, n)));
}
__device__ __forceinline__ float silu_bf(float v) {
    float s = __fdividef(v, 1.0f + __expf(-v));
    return bf_lo(pack2(s, 0.f));
}
__device__ __forceinline__ void bar_sync(int id, int n) { asm volatile("bar.sync %0, %1;" ::"r"(id), "r"(n) : "memory"); }
__device__ __forceinline__ void bar_arrive(int id, int n) { asm volatile("bar.arrive %0, %1;" ::"r"(id), "r"(n) : "memory"); }
__device__ __forceinline__ void fence_async_smem() { asm volatile("fence.proxy.async.shared::cta;" ::: "memory"); }
__device__ __forceinline__ uint64_t mk_desc(uint32_t addr, uint32_t lbo, uint32_t sbo, uint32_t swz) {
    const uint32_t lo = (addr >> 4) + ((lbo >> 4) << 16);
    const uint32_t hi = (sbo >> 4) | (swz << 30);
    return ((uint64_t)hi << 32) | lo;
}
__device__ __forceinline__ uint64_t mk_desc16(uint32_t a16, uint32_t off, uint32_t lbo, uint32_t sbo, uint32_t swz) {
    const uint32_t lo = a16 + ((off >> 4) + ((lbo >> 4) << 16));
    const uint32_t hi = (sbo >> 4) | (swz << 30);
    return ((uint64_t)hi << 32) | lo;
}
#define WG_FENCE() asm volatile("wgmma.fence.sync.aligned;" ::: "memory")
#define WG_COMMIT() asm volatile("wgmma.commit_group.sync.aligned;" ::: "memory")
#define WG_WAIT(n) asm volatile("wgmma.wait_group.sync.aligned %0;" ::"n"(n) : "memory")
template <int N> __device__ __forceinline__ void pin(float (&d)[N]) {
#pragma unroll
    for (int i = 0; i < N; i++) asm volatile("" : "+f"(d[i])::"memory");
}
__device__ __forceinline__ void pin(uint32_t (&a)[4]) {
    asm volatile("" : "+r"(a[0]), "+r"(a[1]), "+r"(a[2]), "+r"(a[3])::"memory");
}

__device__ __forceinline__ void wgmma_n8_t1(float (&d)[4], const uint32_t (&a)[4], uint64_t descB, int scaleD) {
    asm volatile("{\n.reg .pred p;\nsetp.ne.b32 p, %9, 0;\n"
        "wgmma.mma_async.sync.aligned.m64n8k16.f32.bf16.bf16 "
        "{%0, %1, %2, %3}, "
        "{%4, %5, %6, %7}, %8, p, 1, 1, 1;\n}\n"
        : "+f"(d[0]), "+f"(d[1]), "+f"(d[2]), "+f"(d[3])
        : "r"(a[0]), "r"(a[1]), "r"(a[2]), "r"(a[3]), "l"(descB), "r"(scaleD));
}
__device__ __forceinline__ void wgmma_n32_t1(float (&d)[16], const uint32_t (&a)[4], uint64_t descB, int scaleD) {
    asm volatile("{\n.reg .pred p;\nsetp.ne.b32 p, %21, 0;\n"
        "wgmma.mma_async.sync.aligned.m64n32k16.f32.bf16.bf16 "
        "{%0, %1, %2, %3, %4, %5, %6, %7, %8, %9, %10, %11, %12, %13, %14, %15}, "
        "{%16, %17, %18, %19}, %20, p, 1, 1, 1;\n}\n"
        : "+f"(d[0]), "+f"(d[1]), "+f"(d[2]), "+f"(d[3]), "+f"(d[4]), "+f"(d[5]), "+f"(d[6]), "+f"(d[7]),
          "+f"(d[8]), "+f"(d[9]), "+f"(d[10]), "+f"(d[11]), "+f"(d[12]), "+f"(d[13]), "+f"(d[14]), "+f"(d[15])
        : "r"(a[0]), "r"(a[1]), "r"(a[2]), "r"(a[3]), "l"(descB), "r"(scaleD));
}
__device__ __forceinline__ void wgmma_n56_t1(float (&d)[28], const uint32_t (&a)[4], uint64_t descB, int scaleD) {
    asm volatile("{\n.reg .pred p;\nsetp.ne.b32 p, %33, 0;\n"
        "wgmma.mma_async.sync.aligned.m64n56k16.f32.bf16.bf16 "
        "{%0, %1, %2, %3, %4, %5, %6, %7, %8, %9, %10, %11, %12, %13, %14, %15, "
        "%16, %17, %18, %19, %20, %21, %22, %23, %24, %25, %26, %27}, "
        "{%28, %29, %30, %31}, %32, p, 1, 1, 1;\n}\n"
        : "+f"(d[0]), "+f"(d[1]), "+f"(d[2]), "+f"(d[3]), "+f"(d[4]), "+f"(d[5]), "+f"(d[6]), "+f"(d[7]),
          "+f"(d[8]), "+f"(d[9]), "+f"(d[10]), "+f"(d[11]), "+f"(d[12]), "+f"(d[13]), "+f"(d[14]), "+f"(d[15]),
          "+f"(d[16]), "+f"(d[17]), "+f"(d[18]), "+f"(d[19]), "+f"(d[20]), "+f"(d[21]), "+f"(d[22]), "+f"(d[23]),
          "+f"(d[24]), "+f"(d[25]), "+f"(d[26]), "+f"(d[27])
        : "r"(a[0]), "r"(a[1]), "r"(a[2]), "r"(a[3]), "l"(descB), "r"(scaleD));
}
__device__ __forceinline__ void wgmma_n64_t0(float (&d)[32], const uint32_t (&a)[4], uint64_t descB, int scaleD) {
    asm volatile("{\n.reg .pred p;\nsetp.ne.b32 p, %37, 0;\n"
        "wgmma.mma_async.sync.aligned.m64n64k16.f32.bf16.bf16 "
        "{%0, %1, %2, %3, %4, %5, %6, %7, %8, %9, %10, %11, %12, %13, %14, %15, "
        "%16, %17, %18, %19, %20, %21, %22, %23, %24, %25, %26, %27, %28, %29, %30, %31}, "
        "{%32, %33, %34, %35}, %36, p, 1, 1, 0;\n}\n"
        : "+f"(d[0]), "+f"(d[1]), "+f"(d[2]), "+f"(d[3]), "+f"(d[4]), "+f"(d[5]), "+f"(d[6]), "+f"(d[7]),
          "+f"(d[8]), "+f"(d[9]), "+f"(d[10]), "+f"(d[11]), "+f"(d[12]), "+f"(d[13]), "+f"(d[14]), "+f"(d[15]),
          "+f"(d[16]), "+f"(d[17]), "+f"(d[18]), "+f"(d[19]), "+f"(d[20]), "+f"(d[21]), "+f"(d[22]), "+f"(d[23]),
          "+f"(d[24]), "+f"(d[25]), "+f"(d[26]), "+f"(d[27]), "+f"(d[28]), "+f"(d[29]), "+f"(d[30]), "+f"(d[31])
        : "r"(a[0]), "r"(a[1]), "r"(a[2]), "r"(a[3]), "l"(descB), "r"(scaleD));
}
__device__ __forceinline__ void wgmma_n64_t1(float (&d)[32], const uint32_t (&a)[4], uint64_t descB, int scaleD) {
    asm volatile("{\n.reg .pred p;\nsetp.ne.b32 p, %37, 0;\n"
        "wgmma.mma_async.sync.aligned.m64n64k16.f32.bf16.bf16 "
        "{%0, %1, %2, %3, %4, %5, %6, %7, %8, %9, %10, %11, %12, %13, %14, %15, "
        "%16, %17, %18, %19, %20, %21, %22, %23, %24, %25, %26, %27, %28, %29, %30, %31}, "
        "{%32, %33, %34, %35}, %36, p, 1, 1, 1;\n}\n"
        : "+f"(d[0]), "+f"(d[1]), "+f"(d[2]), "+f"(d[3]), "+f"(d[4]), "+f"(d[5]), "+f"(d[6]), "+f"(d[7]),
          "+f"(d[8]), "+f"(d[9]), "+f"(d[10]), "+f"(d[11]), "+f"(d[12]), "+f"(d[13]), "+f"(d[14]), "+f"(d[15]),
          "+f"(d[16]), "+f"(d[17]), "+f"(d[18]), "+f"(d[19]), "+f"(d[20]), "+f"(d[21]), "+f"(d[22]), "+f"(d[23]),
          "+f"(d[24]), "+f"(d[25]), "+f"(d[26]), "+f"(d[27]), "+f"(d[28]), "+f"(d[29]), "+f"(d[30]), "+f"(d[31])
        : "r"(a[0]), "r"(a[1]), "r"(a[2]), "r"(a[3]), "l"(descB), "r"(scaleD));
}
__device__ __forceinline__ void wgmma_n128_t1(float (&d)[64], const uint32_t (&a)[4], uint64_t descB, int scaleD) {
    asm volatile("{\n.reg .pred p;\nsetp.ne.b32 p, %69, 0;\n"
        "wgmma.mma_async.sync.aligned.m64n128k16.f32.bf16.bf16 "
        "{%0, %1, %2, %3, %4, %5, %6, %7, %8, %9, %10, %11, %12, %13, %14, %15, "
        "%16, %17, %18, %19, %20, %21, %22, %23, %24, %25, %26, %27, %28, %29, %30, %31, "
        "%32, %33, %34, %35, %36, %37, %38, %39, %40, %41, %42, %43, %44, %45, %46, %47, "
        "%48, %49, %50, %51, %52, %53, %54, %55, %56, %57, %58, %59, %60, %61, %62, %63}, "
        "{%64, %65, %66, %67}, %68, p, 1, 1, 1;\n}\n"
        : "+f"(d[0]), "+f"(d[1]), "+f"(d[2]), "+f"(d[3]), "+f"(d[4]), "+f"(d[5]), "+f"(d[6]), "+f"(d[7]),
          "+f"(d[8]), "+f"(d[9]), "+f"(d[10]), "+f"(d[11]), "+f"(d[12]), "+f"(d[13]), "+f"(d[14]), "+f"(d[15]),
          "+f"(d[16]), "+f"(d[17]), "+f"(d[18]), "+f"(d[19]), "+f"(d[20]), "+f"(d[21]), "+f"(d[22]), "+f"(d[23]),
          "+f"(d[24]), "+f"(d[25]), "+f"(d[26]), "+f"(d[27]), "+f"(d[28]), "+f"(d[29]), "+f"(d[30]), "+f"(d[31]),
          "+f"(d[32]), "+f"(d[33]), "+f"(d[34]), "+f"(d[35]), "+f"(d[36]), "+f"(d[37]), "+f"(d[38]), "+f"(d[39]),
          "+f"(d[40]), "+f"(d[41]), "+f"(d[42]), "+f"(d[43]), "+f"(d[44]), "+f"(d[45]), "+f"(d[46]), "+f"(d[47]),
          "+f"(d[48]), "+f"(d[49]), "+f"(d[50]), "+f"(d[51]), "+f"(d[52]), "+f"(d[53]), "+f"(d[54]), "+f"(d[55]),
          "+f"(d[56]), "+f"(d[57]), "+f"(d[58]), "+f"(d[59]), "+f"(d[60]), "+f"(d[61]), "+f"(d[62]), "+f"(d[63])
        : "r"(a[0]), "r"(a[1]), "r"(a[2]), "r"(a[3]), "l"(descB), "r"(scaleD));
}

#define TG(k) do {} while (0)
#define TS(k) do {} while (0)

__device__ __forceinline__ void publish14(uint4* dst, const uint32_t (&r)[14], uint32_t tag) {
    st_rlx128(dst + 0 * 128, r[0], r[1], r[2], prmt(r[3], tag, 0x1054));
    st_rlx128(dst + 1 * 128, r[4], r[5], r[6], prmt(r[7], tag, 0x1054));
    st_rlx128(dst + 2 * 128, r[8], r[9], r[10], prmt(r[11], tag, 0x1054));
    st_rlx128(dst + 3 * 128, r[12], r[13], prmt(r[3], r[7], 0x7632), prmt(r[11], tag, 0x3254));
}
__device__ __forceinline__ uint32_t tag_bad(const uint4 (&v)[4], uint32_t tag) {
    return ((v[0].w ^ tag) | (v[1].w ^ tag) | (v[2].w ^ tag) | (v[3].w ^ tag)) & 0xFFFFu;
}
__device__ __forceinline__ void unpack14(const uint4 (&v)[4], uint32_t (&r)[14]) {
    r[0] = v[0].x; r[1] = v[0].y; r[2] = v[0].z; r[3] = prmt(v[0].w, v[3].z, 0x5432);
    r[4] = v[1].x; r[5] = v[1].y; r[6] = v[1].z; r[7] = prmt(v[1].w, v[3].z, 0x7632);
    r[8] = v[2].x; r[9] = v[2].y; r[10] = v[2].z; r[11] = prmt(v[2].w, v[3].w, 0x7632);
    r[12] = v[3].x; r[13] = v[3].y;
}
template <int ODD> __host__ __device__ constexpr int kstep_group(int s) {
    return s == 6 ? ODD : (s / 3) * 7 + 2 * (s % 3) + (2 * (s % 3) >= ODD ? 1 : 0);
}
__host__ __device__ constexpr int kstep_gap(int s) { return s == 6 ? 7 : 1; }
__device__ __forceinline__ bool gather_try(uint4 (&v)[4][4], const uint4* src, uint32_t tag) {
#pragma unroll
    for (int s = 0; s < 4; s++)
#pragma unroll
        for (int k = 0; k < 4; k++) v[s][k] = ld_rlx128(src + (s * 4 + k) * 128);
    uint32_t bad = 0;
#pragma unroll
    for (int s = 0; s < 4; s++) bad |= tag_bad(v[s], tag);
    return __any_sync(0xFFFFFFFFu, bad != 0);
}
__device__ __forceinline__ uint32_t st_tag(uint2 v) { return prmt(v.x, v.y, 0x4440) & 0xFFFFu; }
__device__ __forceinline__ float reduce8(float (&a)[8], int lane) {
    {
        bool up = lane & 16;
#pragma unroll
        for (int i = 0; i < 4; i++) {
            float keep = up ? a[i + 4] : a[i], send = up ? a[i] : a[i + 4];
            a[i] = keep + __shfl_xor_sync(0xFFFFFFFFu, send, 16);
        }
    }
    {
        bool up = lane & 8;
#pragma unroll
        for (int i = 0; i < 2; i++) {
            float keep = up ? a[i + 2] : a[i], send = up ? a[i] : a[i + 2];
            a[i] = keep + __shfl_xor_sync(0xFFFFFFFFu, send, 8);
        }
    }
    {
        bool up = lane & 4;
        float keep = up ? a[1] : a[0], send = up ? a[0] : a[1];
        a[0] = keep + __shfl_xor_sync(0xFFFFFFFFu, send, 4);
    }
    return a[0];
}
__device__ __forceinline__ void fma8(float (&a)[8], float s, uint4 w) {
    a[0] = fmaf(s, bf_lo(w.x), a[0]); a[1] = fmaf(s, bf_hi(w.x), a[1]);
    a[2] = fmaf(s, bf_lo(w.y), a[2]); a[3] = fmaf(s, bf_hi(w.y), a[3]);
    a[4] = fmaf(s, bf_lo(w.z), a[4]); a[5] = fmaf(s, bf_hi(w.z), a[5]);
    a[6] = fmaf(s, bf_lo(w.w), a[6]); a[7] = fmaf(s, bf_hi(w.w), a[7]);
}
__device__ __forceinline__ float quad_sum(float v) {
    v += __shfl_xor_sync(0xFFFFFFFFu, v, 1);
    v += __shfl_xor_sync(0xFFFFFFFFu, v, 2);
    return v;
}
__device__ __forceinline__ float quad_max(float v) {
    v = fmaxf(v, __shfl_xor_sync(0xFFFFFFFFu, v, 1));
    v = fmaxf(v, __shfl_xor_sync(0xFFFFFFFFu, v, 2));
    return v;
}
__device__ __forceinline__ void store_kv(uint32_t tile_addr, const float (&acc)[28], int warp, int lane) {
    uint32_t a = tile_addr + (lane >> 4) * 1024 + (2 * warp + ((lane >> 3) & 1)) * 128 + (lane & 7) * 16;
#pragma unroll
    for (int i = 0; i < 3; i++)
        stsm4(a + i * 2048, pack2(acc[8 * i + 0], acc[8 * i + 1]), pack2(acc[8 * i + 2], acc[8 * i + 3]),
              pack2(acc[8 * i + 4], acc[8 * i + 5]), pack2(acc[8 * i + 6], acc[8 * i + 7]));
    uint32_t a2 = tile_addr + 6 * 1024 + (2 * warp + ((lane >> 3) & 1)) * 128 + (lane & 7) * 16;
    stsm2(a2, pack2(acc[24], acc[25]), pack2(acc[26], acc[27]));
}

#define PV_SPLIT 2
#define TOKEN_KK 1
template <int V> struct IC { static constexpr int value = V; };
constexpr int N_GU3 = 0, N_GU = 2, N_DN = 14, N_ITEMS = 22;

template <int H>
__device__ __forceinline__ void landed_read(uint4 (&v)[4][4], uint32_t main_addr, uint32_t ext_addr, const uint4* src, uint32_t tag) {
#pragma unroll
    for (int s = 0; s < 4; s++)
#pragma unroll
        for (int k = 0; k < 4; k++) v[s][k] = lds128((4 * H + s < 7 ? main_addr + (4 * H + s) * 8192 : ext_addr) + k * 2048);
    uint32_t bad = 0;
#pragma unroll
    for (int s = 0; s < 4; s++) bad |= tag_bad(v[s], tag);
    if (__builtin_expect(__any_sync(0xFFFFFFFFu, bad != 0), 0)) {
        int it = 0;
#pragma unroll 1
        while (gather_try(v, src + H * 2048, tag) && ++it < SPIN_LIMIT) {}
    }
}
__device__ __forceinline__ void gather_issue(const uint4* src, const uint2* st, uint32_t tag, int lane, uint32_t main_addr,
                                             uint32_t ext_addr, uint32_t st_addr, uint32_t bar) {
    const int s = lane >> 2;
    if (lane == 0) mbar_expect_tx(bar, st ? 65536 + 4096 : 65536);
    __syncwarp();
    const uint32_t* p = (const uint32_t*)(src + (s * 4 + 3) * 128 + (lane & 3) * 32 + 31) + 3;
    uint32_t todo = 0x11111111u;
    int it = 0;
#pragma unroll 1
    while (todo && ++it < SPIN_LIMIT) {
        uint32_t bad;
        if (st) bad = st_tag(ld_rlx64(st + s * 64 + (lane & 3) * 16 + 15)) ^ tag;
        else bad = (ld_rlx32(p) ^ tag) | (ld_rlx32(p - 2 * 128 * 4) ^ tag);
        uint32_t ok = __ballot_sync(0xFFFFFFFFu, (bad & 0xFFFFu) == 0);
        ok &= ok >> 1;
        ok &= ok >> 2;
        ok &= todo;
        if ((ok >> lane) & 1u) {
            bulk_g2s(s < 7 ? main_addr + s * 8192 : ext_addr, src + s * 512, 8192, bar);
            if (st) bulk_g2s(st_addr + s * 512, st + s * 64, 512, bar);
        }
        todo &= ~ok;
    }
}
__device__ __forceinline__ int tile_imax(const float (&s)[32], int o) {
    int a = __vimax3_s32(__float_as_int(s[o]), __float_as_int(s[o + 1]), __float_as_int(s[4 + o]));
    int c = __vimax3_s32(__float_as_int(s[16 + o]), __float_as_int(s[17 + o]), __float_as_int(s[20 + o]));
    a = __vimax3_s32(a, __float_as_int(s[5 + o]), __float_as_int(s[8 + o]));
    c = __vimax3_s32(c, __float_as_int(s[21 + o]), __float_as_int(s[24 + o]));
    a = __vimax3_s32(a, __float_as_int(s[9 + o]), __float_as_int(s[12 + o]));
    c = __vimax3_s32(c, __float_as_int(s[25 + o]), __float_as_int(s[28 + o]));
    a = __vimax3_s32(a, __float_as_int(s[13 + o]), __float_as_int(s[29 + o]));
    return max(a, c);
}
template <int A, int B> __device__ __forceinline__ void init_bars() {
#pragma unroll
    for (int i = A; i < B; i++) mbar_init(BAR(i), i < N_ONE ? 1 : (i < N_EIGHT ? 8 : 4));
}
__device__ __forceinline__ uint32_t perm_off(int p) {
    const int blk = p >> 2, q = p & 3;
    return ((blk >> 2) * 16 + q * 4 + (blk & 3)) * 4;
}

__global__ void __launch_bounds__(NTHREADS, 1)
fused_block_kernel(Scratch* __restrict__ scr, const __nv_bfloat16* __restrict__ x, const __nv_bfloat16* __restrict__ cvec,
                   const __nv_bfloat16* __restrict__ wmod, __nv_bfloat16* __restrict__ out, const __nv_bfloat16* __restrict__ wqkv, const __nv_bfloat16* __restrict__ wo,
                   const __nv_bfloat16* __restrict__ wg, const __nv_bfloat16* __restrict__ wu, const __nv_bfloat16* __restrict__ wd,
                   const __grid_constant__ CUtensorMap tm_x, const __grid_constant__ CUtensorMap tm_qkv,
                   const __grid_constant__ CUtensorMap tm_wo, const __grid_constant__ CUtensorMap tm_g,
                   const __grid_constant__ CUtensorMap tm_u, const __grid_constant__ CUtensorMap tm_g3,
                   const __grid_constant__ CUtensorMap tm_u3, const __grid_constant__ CUtensorMap tm_d,
                   const __grid_constant__ CUtensorMap tm_m) {
    extern __shared__ __align__(1024) uint8_t smem_raw[];
    const int bid = blockIdx.x;
    const int j = (bid & 3) + 4 * (bid >> 6);
    const int b = (bid & 63) >> 2;
    const int tid = threadIdx.x;
    const int lane = tid & 31;
    if (smem_u32(smem_raw) != SB) return;
    TS(0);
    TG(30);
    const int qcol = 56 * j - 8 * (j & 1);
    const int wgi = __shfl_sync(0xFFFFFFFFu, tid >> 7, 0);
    if (wgi == 2) {
        asm volatile("setmaxnreg.dec.sync.aligned.u32 40;");
        const int hw = __shfl_sync(0xFFFFFFFFu, (tid - 256) >> 5, 0);
        if (lane == 0) {
            if (hw == 0) {
                asm volatile("prefetch.tensormap [%0];" ::"l"(&tm_x) : "memory");
                asm volatile("prefetch.tensormap [%0];" ::"l"(&tm_qkv) : "memory");
                init_bars<0, F_HK>();
            }
            if (hw == 1) init_bars<F_HK, F_RING>();
            if (hw == 2) init_bars<F_RING, E_RING>();
            if (hw == 3) init_bars<E_RING, N_BARS>();
            asm volatile("fence.mbarrier_init.release.cluster;" ::: "memory");
        }
        __syncwarp();
        bar_arrive(2, 384);
        if (hw == 0) bar_arrive(3, 128);
        else { bar_arrive(7, 128); bar_sync(3, 128); }
        uint32_t tag = 0;
        if (hw != 0) tag = ld_rlx32(&scr->epoch[bid * 32 + lane]);
        if (hw == 0) {
            if (lane == 0) {
                TS(1);
                mbar_expect_tx(BAR(F_X0), 4 * 16384);
                mbar_expect_tx(BAR(F_X0 + 1), 3 * 16384);
#pragma unroll
                for (int c = 0; c < 7; c++) tma_2d(SLOTA(3) + c * 16384, &tm_x, 64 * c, 128 * b, BAR(F_X0 + (c >= 4)));
#pragma unroll
                for (int i = F_K0; i <= F_Q1; i++) mbar_expect_tx(BAR(i), SLOT);
                tma_2d(SLOTA(0), &tm_qkv, DM + qcol, 0, BAR(F_K0));
                tma_2d(SLOTA(1), &tm_qkv, DM + qcol, 224, BAR(F_K1));
                tma_2d(SLOTA(2), &tm_qkv, 2 * DM + qcol, 0, BAR(F_V0));
                TS(2);
            }
            bar_sync(7, 128);
            if (lane == 0) {
                mbar_wait(BAR(R_X), 0);
                tma_2d(SLOTA(3), &tm_qkv, 2 * DM + qcol, 224, BAR(F_V1));
                tma_2d(SLOTA(4), &tm_qkv, qcol, 0, BAR(F_Q0));
                tma_2d(SLOTA(5), &tm_qkv, qcol, 224, BAR(F_Q1));
                TS(3);
                mbar_wait(BAR(R_V), 0);
                mbar_expect_tx(BAR(F_WO0), SLOT);
                mbar_expect_tx(BAR(F_WO1), SLOT);
                mbar_wait(BAR(F_HV), 0);
                tma_2d(SLOTA(2), &tm_wo, qcol, 0, BAR(F_WO0));
                tma_2d(SLOTA(3), &tm_wo, qcol, 224, BAR(F_WO1));
                int pos = 0, use = 0;
#pragma unroll 1
                for (int n = 0; n < N_ITEMS; n++) {
                    const uint32_t full = BAR(F_RING) + 8 * pos;
                    const uint32_t dst = SB + ring_slot(pos) * SLOT;
                    if (use == 0) mbar_wait(BAR(n == 0 ? R_ATT : (n < 3 ? R_WO : (n < 5 ? R_Y0 : R_Y1))), 0);
                    else mbar_wait(BAR(E_RING) + 8 * pos, (use - 1) & 1);
                    mbar_expect_tx(full, SLOT);
                    if (n < N_GU) {
                        const int col = 224 * j + ((j & 1) ? 0 : 192), row = 224 * n;
                        tma_2d(dst, &tm_g3, col, row, full);
                        tma_2d(dst + SLOT / 2, &tm_u3, col, row, full);
                    } else if (n < N_DN) {
                        const int m = n - N_GU;
                        const int col = 224 * j + 32 * (j & 1) + 64 * (m >> 2), row = 112 * (m & 3);
                        tma_2d(dst, &tm_g, col, row, full);
                        tma_2d(dst + SLOT / 2, &tm_u, col, row, full);
                    } else {
                        const int m = n - N_DN;
                        const int k = (0x33221010 >> (4 * m)) & 3, par = (0xAC >> m) & 1;
                        const int sl = (j + 2 * k + 2) & 7;
                        tma_2d(dst, &tm_d, 56 * sl - 8 * (sl & 1), 224 * (j ^ par), full);
                    }
                    if (++pos == NSLOT) { pos = 0; use++; }
                }
            }
            return;
        }
        if (hw == 1) {
            if (lane == 0) {
                mbar_wait(BAR(F_X0 + 1), 0);
                l2_prefetch((const uint8_t*)wqkv + bid * 9408, 9408);
                mbar_wait(BAR(F_V0), 0);
                l2_prefetch((const uint8_t*)wo + bid * 3136, 3136);
                l2_prefetch((const uint8_t*)wg + bid * 12544, 12544);
                l2_prefetch((const uint8_t*)wu + bid * 12544, 12544);
                l2_prefetch((const uint8_t*)wd + bid * 12544, 12544);
            }
            tag += 1;
            if (lane == 0) {
#pragma unroll 1
                for (int m = 0; m < 2; m++) {
                    mbar_wait(BAR(R_KST) + 8 * m, 0);
                    const int idx = (b * 8 + j) * 2 + m;
                    bulk_s2g(scr->kv + (size_t)idx * 2 * KVT, SLOTA(6) + m * 2 * KVT, 2 * KVT);
                    asm volatile("cp.async.bulk.commit_group;" ::: "memory");
                    asm volatile("cp.async.bulk.wait_group 0;" ::: "memory");
                    asm volatile("st.relaxed.gpu.global.u32 [%0], %1;" ::"l"(&scr->kvflag[idx * 8]), "r"(tag) : "memory");
                }
            }
            __syncwarp();
            mbar_wait(BAR(R_Q), 0);
            gather_issue(scr->o + (size_t)(2 * b) * 4096, nullptr, tag, lane, SLOTA(4), SB + OFF_QX + 16384, 0, BAR(F_O0));
            mbar_wait(BAR(R_O0), 0);
            mbar_wait(BAR(R_ATT), 0);
            gather_issue(scr->x2 + (size_t)(2 * b) * 4096, scr->st2 + (2 * b) * 512, tag, lane, SLOTA(4), SB + OFF_QX + 16384,
                         SB + OFF_QX + 12288, BAR(F_Y0));
            return;
        }
        if (hw == 2) {
            tag += 1;
            const int nh = b < 2 ? b : 2;
            mbar_wait(BAR(R_K), 0);
            if (nh < 2) {
                const uint32_t bytes = (2 - nh) * 2 * KVT;
#pragma unroll 1
                for (uint32_t o = lane * 16; o < bytes; o += 512) {
                    sts128(SLOTA(0) + o, 0, 0, 0, 0);
                    sts128(SLOTA(1) + o, 0, 0, 0, 0);
                }
                fence_async_smem();
                __syncwarp();
            }
            if (lane == 0) {
                mbar_expect_tx(BAR(F_HK), nh * 2 * KVT);
                mbar_expect_tx(BAR(F_HV), nh * 2 * KVT);
            }
            __syncwarp();
            {
                const int m = (lane >> 1) & 1, h = lane & 1;
                const int idx = ((b - 2 + h) * 8 + j) * 2 + m;
                bool todo = lane < 4 && h >= 2 - nh;
                int it = 0;
#pragma unroll 1
                while (__any_sync(0xFFFFFFFFu, todo) && ++it < SPIN_LIMIT) {
                    if (todo && ld_rlx32(&scr->kvflag[idx * 8]) == tag) {
                        bulk_g2s(SLOTA(0) + m * SLOT + h * 2 * KVT, scr->kv + (size_t)idx * 2 * KVT, 2 * KVT, BAR(F_HK) + 8 * m);
                        todo = false;
                    }
                }
            }
            mbar_wait(BAR(R_ATT), 0);
            gather_issue(scr->o + (size_t)(2 * b + 1) * 4096, nullptr, tag, lane, SLOTA(0), SB + OFF_QX, 0, BAR(F_O1));
            mbar_wait(BAR(R_O1), 0);
            gather_issue(scr->x2 + (size_t)(2 * b + 1) * 4096, scr->st2 + (2 * b + 1) * 512, tag, lane, SLOTA(0), SB + OFF_QX,
                         SB + OFF_QX + 8192, BAR(F_Y1));
        } else {
            tag += 1;
            if (bid < 112) {
                const int col = 896 + bid * 16 + (lane & 1) * 8;
                const uint32_t slab = SB + OFF_QX, sil = SB + OFF_QX + 14336;
#pragma unroll
                for (int i = 0; i < 7; i++) {
                    const uint32_t cc = ((const uint32_t*)cvec)[lane + 32 * i];
                    sts32(sil + (lane + 32 * i) * 8, __float_as_uint(silu_bf(bf_lo(cc))));
                    sts32(sil + (lane + 32 * i) * 8 + 4, __float_as_uint(silu_bf(bf_hi(cc))));
                }
                mbar_wait(BAR(F_V0), 0);
                if (lane == 0) {
                    mbar_expect_tx(BAR(F_WM), 14336);
                    tma_2d(slab, &tm_m, 896 + bid * 16, 0, BAR(F_WM));
                    tma_2d(slab + 7168, &tm_m, 896 + bid * 16, 224, BAR(F_WM));
                }
                __syncwarp();
                mbar_wait(BAR(F_WM), 0);
                float a[8];
#pragma unroll
                for (int i = 0; i < 8; i++) a[i] = 0.f;
#pragma unroll 4
                for (int i = 0; i < 28; i++)
                    fma8(a, __uint_as_float(lds32(sil + ((lane >> 1) + 16 * i) * 4)), lds128(slab + i * 512 + lane * 16));
                {
                    bool up = lane & 16;
#pragma unroll
                    for (int i = 0; i < 4; i++) {
                        float keep = up ? a[i + 4] : a[i], send = up ? a[i] : a[i + 4];
                        a[i] = keep + __shfl_xor_sync(0xFFFFFFFFu, send, 16);
                    }
                    up = lane & 8;
#pragma unroll
                    for (int i = 0; i < 2; i++) {
                        float keep = up ? a[i + 2] : a[i], send = up ? a[i] : a[i + 2];
                        a[i] = keep + __shfl_xor_sync(0xFFFFFFFFu, send, 8);
                    }
#pragma unroll
                    for (int o = 2; o < 8; o <<= 1) {
                        a[0] += __shfl_xor_sync(0xFFFFFFFFu, a[0], o);
                        a[1] += __shfl_xor_sync(0xFFFFFFFFu, a[1], o);
                    }
                }
                if ((lane & 6) == 0) st_rlx64(&scr->mod[(col >> 1) + (lane >> 3)], pack2(a[0], a[1]), tag);
            }
            __syncwarp();
            if (lane == 0) mbar_arrive(BAR(R_WM));
#pragma unroll 1
            for (int h = 0; h < 2; h++) {
                uint2 mv[8];
                int it = 0;
                uint32_t bad;
#pragma unroll 1
                do {
                    bad = 0;
#pragma unroll
                    for (int i = 0; i < 7; i++) mv[i] = ld_rlx64(&scr->mod[672 + 224 * h + lane + 32 * i]);
                    mv[7] = ld_rlx64(&scr->mod[448 + 672 * h + 28 * j + (lane < 28 ? lane : 0)]);
#pragma unroll
                    for (int i = 0; i < 8; i++) bad |= mv[i].y ^ tag;
                } while (bad && ++it < SPIN_LIMIT);
#pragma unroll
                for (int i = 0; i < 7; i++)
                    sts32(SB + (h ? OFF_C2 : OFF_S2) + perm_off(lane + 32 * i), h ? hfma2(mv[i].x, 0x3F803F80u, 0x3F803F80u) : mv[i].x);
                if (lane < 28) sts32(SB + (h ? OFF_GB : OFF_GA) + lane * 4, mv[7].x);
            }
            __syncwarp();
            if (lane == 0) mbar_arrive(BAR(F_MOD2));
        }
    } else {
        const int w = wgi, t = tid & 127, warp = t >> 5, r = lane >> 2, q = lane & 3;
        const int tile = 2 * b + w;
        const int row0 = 64 * tile + 16 * warp + r;
        const uint32_t jo = j & 1;

        const int mt = bid < 112 ? bid : 111;
        const int mcg = mt % 28, mrs = mt / 28;
        const int mrow = 112 * mrs + (tid >> 2), mrow1 = tid < 192 ? mrow + 64 : mrow;
        const uint4 wm0 = ldg128(wmod + (size_t)mrow * 2688 + mcg * 32 + (tid & 3) * 8);
        const uint4 wm1 = ldg128(wmod + (size_t)mrow1 * 2688 + mcg * 32 + (tid & 3) * 8);
        unsigned short cv0, cv1;
        asm volatile("ld.global.nc.u16 %0, [%1];" : "=h"(cv0) : "l"(cvec + mrow));
        asm volatile("ld.global.nc.u16 %0, [%1];" : "=h"(cv1) : "l"(cvec + mrow1));
        uint32_t tag = ld_rlx32(&scr->epoch[bid * 32 + lane]);
        TS(12);
        tag += 1;
        if (bid < 112) {
            float a[8];
#pragma unroll
            for (int i = 0; i < 8; i++) a[i] = 0.f;
            fma8(a, silu_bf(bf_lo(cv0)), wm0);
            fma8(a, tid < 192 ? silu_bf(bf_lo(cv1)) : 0.f, wm1);
            const float v = reduce8(a, lane);
            sts32(SB + OFF_RED + ((tid >> 5) * 32 + 8 * (lane & 3) + (lane >> 2)) * 4, __float_as_uint(v));
            if (tid < 32) {
                bar_sync(1, 256);
                if (lane < 8) {
                    float4 acc = make_float4(0.f, 0.f, 0.f, 0.f);
#pragma unroll
                    for (int k = 0; k < 8; k++) {
                        const uint4 u = lds128(SB + OFF_RED + k * 128 + lane * 16);
                        acc.x += __uint_as_float(u.x); acc.y += __uint_as_float(u.y);
                        acc.z += __uint_as_float(u.z); acc.w += __uint_as_float(u.w);
                    }
                    st_rlx128(&scr->modp[mrs * 224 + mcg * 8 + lane], (__float_as_uint(acc.x) & ~15u) | (tag & 15u),
                              (__float_as_uint(acc.y) & ~15u) | ((tag >> 4) & 15u), (__float_as_uint(acc.z) & ~15u) | ((tag >> 8) & 15u),
                              (__float_as_uint(acc.w) & ~15u) | ((tag >> 12) & 15u));
                }
                __syncwarp();
            } else {
                bar_arrive(1, 256);
            }
        }
        TS(13);
        asm volatile("setmaxnreg.inc.sync.aligned.u32 232;");
        bar_sync(2, 384);
        uint32_t rn1[4];
        uint32_t af[28][4];
        {
            const int xr_ = 64 * w + 16 * warp + (lane & 7) + 8 * ((lane >> 3) & 1);
            const uint32_t xa = SLOTA(3) + xr_ * 128;
            const uint32_t hi = lane >> 4, sw = lane & 7;
            float c1[2][4], c2[2][4], c3[2][4];
#pragma unroll
            for (int i = 0; i < 4; i++) c1[0][i] = c1[1][i] = c2[0][i] = c2[1][i] = c3[0][i] = c3[1][i] = 0.f;
#pragma unroll
            for (int g = 0; g < 2; g++) {
                const int s0 = 16 * g, s1 = g ? 28 : 16;
                mbar_wait(BAR(F_X0 + g), 0);
#pragma unroll
                for (int s = s0; s < s1; s++) ldsm4(af[s], xa + (s >> 2) * 16384 + (((2 * (s & 3) + hi) ^ sw) << 4));
                if (g == 1) {
                    __syncwarp();
                    if (lane == 0) mbar_arrive(BAR(R_X));
                }
#pragma unroll
                for (int s = s0; s < s1; s++) {
                    hmma(c1[s & 1], af[s], af[s][0], af[s][2]);
                    hmma(c2[s & 1], af[s], af[s][1], af[s][3]);
                    hmma(c3[s & 1], af[s], 0x3F803F80u, 0x3F803F80u);
                }
            }
            TS(14);
            const int src = (lane & ~3) | (r >> 1);
            const float qa = __shfl_sync(0xFFFFFFFFu, (r & 1) ? c1[0][1] + c1[1][1] : c1[0][0] + c1[1][0], src);
            const float qb = __shfl_sync(0xFFFFFFFFu, (r & 1) ? c2[0][3] + c2[1][3] : c2[0][2] + c2[1][2], src);
            const float ma = (c3[0][0] + c3[1][0]) * (1.0f / DM), mb = (c3[0][2] + c3[1][2]) * (1.0f / DM);
            const float rsa = bf_lo(pack2(rsqrtf(fmaxf(fmaf(-ma, ma, qa * (1.0f / DM)), 0.f) + 1e-5f), 0.f));
            const float rsb = bf_lo(pack2(rsqrtf(fmaxf(fmaf(-mb, mb, qb * (1.0f / DM)), 0.f) + 1e-5f), 0.f));
            rn1[0] = pack2(rsa, rsa); rn1[1] = pack2(-ma * rsa, -ma * rsa);
            rn1[2] = pack2(rsb, rsb); rn1[3] = pack2(-mb * rsb, -mb * rsb);
        }
        {
            uint4 mp[4];
            const int mi = tid < 224 ? tid : 0;
#pragma unroll
            for (int k = 0; k < 4; k++) mp[k] = ld_rlx128(&scr->modp[k * 224 + mi]);
#pragma unroll
            for (int s = 0; s < 28; s++) {
                af[s][0] = hfma2(af[s][0], rn1[0], rn1[1]);
                af[s][1] = hfma2(af[s][1], rn1[2], rn1[3]);
                af[s][2] = hfma2(af[s][2], rn1[0], rn1[1]);
                af[s][3] = hfma2(af[s][3], rn1[2], rn1[3]);
                pin(af[s]);
            }
            int it = 0;
            uint32_t bad;
#pragma unroll 1
            while (true) {
                bad = 0;
#pragma unroll
                for (int k = 0; k < 4; k++)
                    bad |= (((mp[k].x & 15u) | ((mp[k].y & 15u) << 4) | ((mp[k].z & 15u) << 8) | ((mp[k].w & 15u) << 12)) ^ tag) & 0xFFFFu;
                if (!bad || ++it > SPIN_LIMIT) break;
#pragma unroll
                for (int k = 0; k < 4; k++) mp[k] = ld_rlx128(&scr->modp[k * 224 + mi]);
            }
            if (tid < 224) {
                float f[4] = {0.f, 0.f, 0.f, 0.f};
#pragma unroll
                for (int k = 0; k < 4; k++) {
                    f[0] += __uint_as_float(mp[k].x & ~15u); f[1] += __uint_as_float(mp[k].y & ~15u);
                    f[2] += __uint_as_float(mp[k].z & ~15u); f[3] += __uint_as_float(mp[k].w & ~15u);
                }
                uint32_t p0 = pack2(f[0], f[1]), p1 = pack2(f[2], f[3]);
                const bool isc = tid >= 112;
                if (isc) { p0 = hfma2(p0, 0x3F803F80u, 0x3F803F80u); p1 = hfma2(p1, 0x3F803F80u, 0x3F803F80u); }
                const int pp = 2 * (isc ? tid - 112 : tid);
                const uint32_t tb = SB + (isc ? OFF_C1 : OFF_S1);
                sts32(tb + perm_off(pp), p0);
                sts32(tb + perm_off(pp + 1), p1);
            }
        }
        bar_sync(1, 256);
        TS(2);

        float accK[28], accV[28], accQ[28];
#pragma unroll
        for (int g = 0; g < 4; g++) {
            const int s0 = 14 * (g >> 1) + 8 * (g & 1), s1 = (g & 1) ? s0 + 6 : s0 + 8;
#pragma unroll
            for (int s = s0; s < s1; s += 2) {
                const uint4 c4 = lds128(SB + OFF_C1 + (s >> 1) * 64 + q * 16), s4 = lds128(SB + OFF_S1 + (s >> 1) * 64 + q * 16);
                af[s][0] = hfma2(af[s][0], c4.x, s4.x);
                af[s][1] = hfma2(af[s][1], c4.x, s4.x);
                af[s][2] = hfma2(af[s][2], c4.y, s4.y);
                af[s][3] = hfma2(af[s][3], c4.y, s4.y);
                af[s + 1][0] = hfma2(af[s + 1][0], c4.z, s4.z);
                af[s + 1][1] = hfma2(af[s + 1][1], c4.z, s4.z);
                af[s + 1][2] = hfma2(af[s + 1][2], c4.w, s4.w);
                af[s + 1][3] = hfma2(af[s + 1][3], c4.w, s4.w);
                pin(af[s]);
                pin(af[s + 1]);
            }
            if ((g & 1) == 0) mbar_wait(BAR(F_K0 + (g >> 1)), 0);
            WG_FENCE();
#pragma unroll
            for (int s = s0; s < s1; s++)
                wgmma_n56_t1(accK, af[s], mk_desc16(jo, SLOTA(s / 14) + (s % 14) * 2048, 0, 1024, 1), s != 0);
        }
        WG_COMMIT();
        mbar_wait(BAR(F_V0), 0);
        WG_FENCE();
#pragma unroll
        for (int s = 0; s < 7; s++) wgmma_n56_t1(accV, af[s], mk_desc16(jo, SLOTA(2) + s * 2048, 0, 1024, 1), s != 0);
        WG_COMMIT();
        mbar_wait(BAR(R_X), 0);
        WG_WAIT(1);
        pin(accK);
        if (lane == 0) mbar_arrive(BAR(R_K));
        store_kv(SLOTA(6) + w * KVT, accK, warp, lane);
        fence_async_smem();
        __syncwarp();
        if (lane == 0) mbar_arrive(BAR(R_KST));
        WG_FENCE();
#pragma unroll
        for (int s = 7; s < 14; s++) wgmma_n56_t1(accV, af[s], mk_desc16(jo, SLOTA(2) + s * 2048, 0, 1024, 1), 1);
        mbar_wait(BAR(F_V1), 0);
        WG_FENCE();
#pragma unroll
        for (int s = 0; s < 14; s++) wgmma_n56_t1(accV, af[14 + s], mk_desc16(jo, SLOTA(3) + s * 2048, 0, 1024, 1), 1);
        WG_COMMIT();
        mbar_wait(BAR(F_Q0), 0);
        WG_FENCE();
#pragma unroll
        for (int s = 0; s < 7; s++) wgmma_n56_t1(accQ, af[s], mk_desc16(jo, SLOTA(4) + s * 2048, 0, 1024, 1), s != 0);
        WG_COMMIT();
        WG_WAIT(1);
        pin(accV);
        if (lane == 0) mbar_arrive(BAR(R_V));
        store_kv(SLOTA(6) + 2 * KVT + w * KVT, accV, warp, lane);
        fence_async_smem();
        __syncwarp();
        if (lane == 0) mbar_arrive(BAR(R_VST));
        WG_FENCE();
#pragma unroll
        for (int s = 7; s < 14; s++) wgmma_n56_t1(accQ, af[s], mk_desc16(jo, SLOTA(4) + s * 2048, 0, 1024, 1), 1);
        mbar_wait(BAR(F_Q1), 0);
        WG_FENCE();
#pragma unroll
        for (int s = 0; s < 14; s++) wgmma_n56_t1(accQ, af[14 + s], mk_desc16(jo, SLOTA(5) + s * 2048, 0, 1024, 1), 1);
        WG_COMMIT();
        WG_WAIT(0);
        pin(accQ);
        if (lane == 0) mbar_arrive(BAR(R_Q));
        mbar_wait(BAR(R_WM), 0);
        {
            uint32_t p[14];
#pragma unroll
            for (int i = 0; i < 14; i++) p[i] = pack2(accQ[2 * i], accQ[2 * i + 1]);
            const uint32_t qa = SB + OFF_QX + w * 8192 + t * 16;
            const bool lo = q < 2;
            sts128(qa, p[0], p[1], p[2], p[3]);
            sts128(qa + 2048, p[4], p[5], lo ? p[6] : 0u, lo ? p[7] : 0u);
            sts128(qa + 4096, lo ? 0u : p[6], lo ? 0u : p[7], p[8], p[9]);
            sts128(qa + 6144, p[10], p[11], p[12], p[13]);
        }
        bar_sync(1, 256);
        TS(3);

        const float SC = 0.18898223650461362f * 1.4426950408889634f;
        const int d0 = 16 * warp + r - 2 * q;
        uint32_t nmask[9];
#pragma unroll
        for (int k = 0; k < 9; k++) {
            asm("shl.b32 %0, %1, %2;" : "=r"(nmask[k]) : "r"(0xFFFFFFFFu), "r"(max(16 * (d0 - 8 * k + 9), 0)));
            asm volatile("" : "+r"(nmask[k]));
        }
#pragma unroll 1
        for (int u = 0; u < 2; u++) {
            uint32_t qf[2][4];
            {
                const uint32_t qa = SB + OFF_QX + u * 8192 + w * 4096 + t * 16;
                const uint4 q0 = lds128(qa), q1 = lds128(qa + 2048);
                qf[0][0] = q0.x; qf[0][1] = q0.y; qf[0][2] = q0.z; qf[0][3] = q0.w;
                qf[1][0] = q1.x; qf[1][1] = q1.y; qf[1][2] = q1.z; qf[1][3] = q1.w;
            }
            const int first = 2 * b + u - 4;
            const uint32_t kh = (SLOTA(0) + u * KVT + w * 3072) >> 4;
            const uint32_t k3 = ((u ? SLOTA(6) : SLOTA(0) + 3 * KVT) + w * 3072) >> 4;
            const uint32_t v3 = ((u ? SLOTA(6) + 2 * KVT : SLOTA(1) + 3 * KVT) + w * 3072) >> 4;
            const uint32_t k4 = (SLOTA(6) + u * KVT + w * 3072) >> 4;
            float s[5][32];
            {
                const float init = first >= 0 ? 0.f : -INFINITY;
#pragma unroll
                for (int i = 0; i < 32; i++) s[0][i] = init;
            }
            pin(s[0]);
            pin(qf[0]);
            pin(qf[1]);
            WG_FENCE();
            wgmma_n64_t0(s[4], qf[0], mk_desc16(k4, 0, 1024, 128, 0), 0);
            wgmma_n64_t0(s[4], qf[1], mk_desc16(k4, 2048, 1024, 128, 0), 1);
            mbar_wait(BAR(F_HK), 0);
            WG_FENCE();
            wgmma_n64_t0(s[0], qf[0], mk_desc16(kh, 0, 1024, 128, 0), 1);
            wgmma_n64_t0(s[0], qf[1], mk_desc16(kh, 2048, 1024, 128, 0), 1);
            WG_COMMIT();
            wgmma_n64_t0(s[3], qf[0], mk_desc16(k3, 0, 1024, 128, 0), 0);
            wgmma_n64_t0(s[3], qf[1], mk_desc16(k3, 2048, 1024, 128, 0), 1);
#pragma unroll
            for (int kt = 2; kt >= 1; kt--) {
                wgmma_n64_t0(s[kt], qf[0], mk_desc16(kh, kt * KVT, 1024, 128, 0), 0);
                wgmma_n64_t0(s[kt], qf[1], mk_desc16(kh, kt * KVT + 2048, 1024, 128, 0), 1);
            }
            WG_COMMIT();
            TS(17);
            WG_WAIT(1);
            pin(s[0]);
            pin(s[4]);
            TS(18);
#pragma unroll
            for (int i = 0; i < 8; i++)
#pragma unroll
                for (int rh = 0; rh < 2; rh++)
#pragma unroll
                    for (int e = 0; e < 2; e++)
                        s[4][4 * i + 2 * rh + e] = (8 * i + e - 8 * rh <= d0) ? s[4][4 * i + 2 * rh + e] : s[0][4 * i + 2 * rh + e];
            int im0 = tile_imax(s[4], 0), im1 = tile_imax(s[4], 2);
            pin(s[4]);
            TS(19);
            WG_WAIT(0);
#pragma unroll
            for (int kt = 1; kt < 4; kt++) pin(s[kt]);
#pragma unroll
            for (int kt = 1; kt < 4; kt++) {
                const int t0 = tile_imax(s[kt], 0), t1 = tile_imax(s[kt], 2);
                if (first + kt >= 0) { im0 = max(im0, t0); im1 = max(im1, t1); }
            }
            im0 = max(im0, __shfl_xor_sync(0xFFFFFFFFu, im0, 1));
            im1 = max(im1, __shfl_xor_sync(0xFFFFFFFFu, im1, 1));
            im0 = max(im0, __shfl_xor_sync(0xFFFFFFFFu, im0, 2));
            im1 = max(im1, __shfl_xor_sync(0xFFFFFFFFu, im1, 2));
            float m0 = __int_as_float(im0), m1 = __int_as_float(im1);
            if (__builtin_expect(__any_sync(0xFFFFFFFFu, (im0 | im1) < 0), 0)) {
                m0 = m1 = -INFINITY;
#pragma unroll
                for (int kt = 1; kt < 5; kt++) {
                    float t0 = -INFINITY, t1 = -INFINITY;
#pragma unroll
                    for (int i = 0; i < 8; i++) {
                        t0 = fmaxf(t0, fmaxf(s[kt][4 * i], s[kt][4 * i + 1]));
                        t1 = fmaxf(t1, fmaxf(s[kt][4 * i + 2], s[kt][4 * i + 3]));
                    }
                    if (kt == 4 || first + kt >= 0) { m0 = fmaxf(m0, t0); m1 = fmaxf(m1, t1); }
                }
                m0 = quad_max(m0);
                m1 = quad_max(m1);
            }
            m0 *= -SC;
            m1 *= -SC;
            TS(20);
            asm volatile("" : "+f"(m0), "+f"(m1)::"memory");
            if (w | u) mbar_wait(BAR(T_TOK) + 8 * (4 * w + warp), w & u);
            TS(21);
            float o[16], ls[2][2] = {{0.f, 0.f}, {0.f, 0.f}};
            uint32_t pf[5][4][4];
#pragma unroll
            for (int kk = 0; kk < 4; kk++) {
                const int kt = kk == 0 ? 4 : 4 - kk;
                const bool ok = kt == 4 || first + kt >= 0;
                const float n0 = ok ? m0 : -INFINITY, n1 = ok ? m1 : -INFINITY;
#pragma unroll
                for (int i = 0; i < 8; i++) {
                    const float p0 = ex2f(fmaf(s[kt][4 * i], SC, n0)), p1 = ex2f(fmaf(s[kt][4 * i + 1], SC, n0));
                    const float p2 = ex2f(fmaf(s[kt][4 * i + 2], SC, n1)), p3 = ex2f(fmaf(s[kt][4 * i + 3], SC, n1));
                    ls[0][0] += p0; ls[0][1] += p1; ls[1][0] += p2; ls[1][1] += p3;
                    pf[kt][i >> 1][2 * (i & 1)] = pack2(p0, p1);
                    pf[kt][i >> 1][2 * (i & 1) + 1] = pack2(p2, p3);
                }
                if (kt == 4) {
#pragma unroll
                    for (int i = 0; i < 8; i++)
#pragma unroll
                        for (int rh = 0; rh < 2; rh++) {
                            const uint32_t pv = pf[4][i >> 1][2 * (i & 1) + rh];
                            pf[0][i >> 1][2 * (i & 1) + rh] = pv & nmask[i - rh + 1];
                            pf[4][i >> 1][2 * (i & 1) + rh] = pv & ~nmask[i - rh + 1];
                        }
                }
                if (kk == TOKEN_KK) {
                    const uint32_t bal = __ballot_sync(0xFFFFFFFFu, pf[kt][3][3] != 0xFFFFFFFFu) | 0x80000000u;
                    if (lane == __ffs(bal) - 1) mbar_arrive(BAR(T_TOK) + 8 * (4 * (1 - w) + warp));
                }
                if (kk == PV_SPLIT || kk == 3) {
#pragma unroll
                    for (int k2 = (kk == 3 && PV_SPLIT >= 0 && PV_SPLIT < 3 ? PV_SPLIT + 1 : 0); k2 <= kk; k2++) {
                        const int t2 = k2 == 0 ? 4 : 4 - k2;
#pragma unroll
                        for (int ks = 0; ks < 4; ks++) pin(pf[t2][ks]);
                        if (t2 == 4) {
#pragma unroll
                            for (int ks = 0; ks < 4; ks++) pin(pf[0][ks]);
                            mbar_wait(BAR(F_HV), 0);
                        }
                    }
                    TS(22 + kk);
                    WG_FENCE();
#pragma unroll
                    for (int k2 = (kk == 3 && PV_SPLIT >= 0 && PV_SPLIT < 3 ? PV_SPLIT + 1 : 0); k2 <= kk; k2++) {
                        const int t2 = k2 == 0 ? 4 : 4 - k2;
#pragma unroll
                        for (int ks = 0; ks < 4; ks++) {
                            const uint64_t dv = t2 == 4 ? mk_desc16(k4, 2 * KVT + ks * 256, 128, 1024, 0)
                                              : t2 == 3 ? mk_desc16(v3, ks * 256, 128, 1024, 0)
                                                        : mk_desc16(kh, SLOT + t2 * KVT + ks * 256, 128, 1024, 0);
                            wgmma_n32_t1(o, pf[t2][ks], dv, (k2 | ks) != 0);
                        }
                        if (t2 == 4) {
#pragma unroll
                            for (int ks = 0; ks < 4; ks++) wgmma_n32_t1(o, pf[0][ks], mk_desc16(kh, SLOT + ks * 256, 128, 1024, 0), 1);
                        }
                    }
                    WG_COMMIT();
                }
            }
            const float il0 = __fdividef(1.0f, quad_sum(ls[0][0] + ls[0][1])), il1 = __fdividef(1.0f, quad_sum(ls[1][0] + ls[1][1]));
            WG_WAIT(0);
            TS(26);
            pin(o);
            uint32_t pk[8];
#pragma unroll
            for (int i = 0; i < 4; i++) {
                pk[2 * i] = pack2(o[4 * i] * il0, o[4 * i + 1] * il0);
                pk[2 * i + 1] = pack2(o[4 * i + 2] * il1, o[4 * i + 3] * il1);
            }
            {
                uint32_t f[6];
#pragma unroll
                for (int i = 0; i < 4; i++) f[i] = w ? pk[i + 4] : pk[i];
                f[4] = w ? pk[2] : pk[4];
                f[5] = w ? pk[3] : pk[5];
                const uint32_t part0 = w ? pk[0] : pk[6], part1 = w ? pk[1] : pk[7];
                const uint32_t got = __shfl_xor_sync(0xFFFFFFFFu, w ? part0 : part1, 2);
                const bool lo = q < 2;
                const uint32_t ex = (lo == (w == 0)) ? (lo ? part0 : part1) : got;
                uint4* dst = scr->o + (((2 * b + u) * 8 + j) * 4 + 2 * w) * 128 + t;
                st_rlx128(dst, f[0], f[1], f[2], prmt(f[3], tag, 0x1054));
                st_rlx128(dst + 128, f[4], f[5], ex, prmt(f[3], tag, 0x3254));
            }
            TS(4 + u);
        }
        if (lane == 0) mbar_arrive(BAR(R_ATT));

        const uint32_t land = (w ? SLOTA(0) : SLOTA(4)) + t * 16, land_x = SB + OFF_QX + (w ? 0 : 16384) + t * 16;
        uint32_t xr[14];
#pragma unroll
        for (int i = 0; i < 7; i++) {
            xr[2 * i] = *(const uint32_t*)(x + (size_t)row0 * DM + 56 * j + 8 * i + 2 * q);
            xr[2 * i + 1] = *(const uint32_t*)(x + (size_t)(row0 + 8) * DM + 56 * j + 8 * i + 2 * q);
        }
        float accO[28];
        mbar_wait(BAR(F_O0) + 8 * w, 0);
        TS(6);
        auto wo_half = [&](auto HC) {
            constexpr int hf = decltype(HC)::value;
            uint4 v[4][4];
            landed_read<hf>(v, land, land_x, scr->o + (size_t)tile * 4096 + t, tag);
            if (hf == 1 && lane == 0) mbar_arrive(BAR(R_O0) + 8 * w);
            const bool lo = q < 2;
#pragma unroll
            for (int s = 0; s < 4; s++) {
                const int k0 = 14 * hf + 7 * (s >> 1) + 3 * (s & 1), k6 = 14 * hf + 7 * (s >> 1) + 6;
                const uint32_t e0 = v[s][1].z, e1 = v[s][3].z;
                const uint32_t got = __shfl_xor_sync(0xFFFFFFFFu, lo ? e1 : e0, 2);
                af[k0][0] = v[s][0].x; af[k0][1] = v[s][0].y; af[k0][2] = v[s][0].z;
                af[k0][3] = prmt(v[s][0].w, v[s][1].w, 0x7632);
                af[k0 + 1][0] = v[s][1].x; af[k0 + 1][1] = v[s][1].y;
                af[k0 + 1][2] = lo ? e0 : got; af[k0 + 1][3] = lo ? got : e1;
                af[k0 + 2][0] = v[s][2].x; af[k0 + 2][1] = v[s][2].y; af[k0 + 2][2] = v[s][2].z;
                af[k0 + 2][3] = prmt(v[s][2].w, v[s][3].w, 0x7632);
                af[k6][2 * (s & 1)] = v[s][3].x; af[k6][2 * (s & 1) + 1] = v[s][3].y;
            }
#pragma unroll
            for (int s = 0; s < 14; s++) pin(af[14 * hf + s]);
            mbar_wait(BAR(F_WO0 + hf), 0);
            WG_FENCE();
#pragma unroll
            for (int s = 0; s < 14; s++)
                wgmma_n56_t1(accO, af[14 * hf + s],
                             mk_desc16(jo, SLOTA(2 + hf) + ((s / 7) * 14 + kstep_group<4>(s % 7)) * 1024, 0, 1024 * kstep_gap(s % 7), 1),
                             (hf | s) != 0);
        };
        wo_half(IC<0>{});
        wo_half(IC<1>{});
        WG_COMMIT();
        mbar_wait(BAR(F_MOD2), 0);
        WG_WAIT(0);
        pin(accO);
        if (lane == 0) mbar_arrive(BAR(R_WO));
        {
            float s0 = 0.f, s1 = 0.f;
#pragma unroll
            for (int i = 0; i < 7; i++) {
                const uint32_t g = lds32(SB + OFF_GA + (4 * i + q) * 4);
                accO[4 * i] = fmaf(bf_lo(g), accO[4 * i], bf_lo(xr[2 * i]));
                accO[4 * i + 1] = fmaf(bf_hi(g), accO[4 * i + 1], bf_hi(xr[2 * i]));
                accO[4 * i + 2] = fmaf(bf_lo(g), accO[4 * i + 2], bf_lo(xr[2 * i + 1]));
                accO[4 * i + 3] = fmaf(bf_hi(g), accO[4 * i + 3], bf_hi(xr[2 * i + 1]));
                s0 += accO[4 * i] + accO[4 * i + 1];
                s1 += accO[4 * i + 2] + accO[4 * i + 3];
            }
            uint32_t p[14];
#pragma unroll
            for (int i = 0; i < 14; i++) p[i] = pack2(accO[2 * i], accO[2 * i + 1]);
            publish14(scr->x2 + ((size_t)tile * 8 + j) * 512 + t, p, tag);
            s0 = quad_sum(s0) * (1.0f / 56);
            s1 = quad_sum(s1) * (1.0f / 56);
            float m0 = 0.f, m1 = 0.f;
#pragma unroll
            for (int i = 0; i < 7; i++) {
                float d;
                d = accO[4 * i] - s0; m0 = fmaf(d, d, m0);
                d = accO[4 * i + 1] - s0; m0 = fmaf(d, d, m0);
                d = accO[4 * i + 2] - s1; m1 = fmaf(d, d, m1);
                d = accO[4 * i + 3] - s1; m1 = fmaf(d, d, m1);
            }
            m0 = quad_sum(m0);
            m1 = quad_sum(m1);
            if (q < 2)
                st_rlx64(scr->st2 + ((size_t)tile * 8 + j) * 64 + 16 * warp + r + 8 * q, prmt(__float_as_uint(q ? s1 : s0), tag, 0x3214),
                         prmt(__float_as_uint(q ? m1 : m0), tag, 0x3215));
        }
        TS(7);

        uint32_t hh[14][4];
        uint4* hout = scr->hx + ((size_t)tile * 8 + j) * 18 * 128 + t;
        const uint32_t hs = SB + OFF_QX + (w ? 0 : 12288) + t * 16;
        {
            uint32_t rn[2][2];
            mbar_wait(BAR(F_Y0) + 8 * w, 0);
            TS(15);
            {
                uint2 st[4];
                const uint32_t sa = SB + OFF_QX + (w ? 8192 : 12288) + (2 * q * 64 + 16 * warp + r) * 8;
                st[0] = lds64(sa); st[1] = lds64(sa + 512); st[2] = lds64(sa + 64); st[3] = lds64(sa + 576);
                const uint2* sp = scr->st2 + ((size_t)tile * 8 + 2 * q) * 64 + 16 * warp + r;
                int it = 0;
#pragma unroll 1
                while (__builtin_expect(__any_sync(0xFFFFFFFFu, (((st_tag(st[0]) ^ tag) | (st_tag(st[1]) ^ tag) | (st_tag(st[2]) ^ tag) |
                                                                  (st_tag(st[3]) ^ tag)) & 0xFFFFu) != 0), 0)) {
                    st[0] = ld_rlx64(sp); st[1] = ld_rlx64(sp + 64); st[2] = ld_rlx64(sp + 8); st[3] = ld_rlx64(sp + 72);
                    if (++it > SPIN_LIMIT) break;
                }
#pragma unroll
                for (int rh = 0; rh < 2; rh++) {
                    const float ma = __uint_as_float(st[2 * rh].x & ~255u), mb = __uint_as_float(st[2 * rh + 1].x & ~255u);
                    const float mean = quad_sum(ma + mb) * 0.125f;
                    const float da = ma - mean, db = mb - mean;
                    const float m2 = quad_sum(__uint_as_float(st[2 * rh].y & ~255u) + __uint_as_float(st[2 * rh + 1].y & ~255u) +
                                              56.f * (da * da + db * db));
                    const float rs = bf_lo(pack2(rsqrtf(m2 * (1.0f / DM) + 1e-5f), 0.f));
                    rn[rh][0] = pack2(rs, rs);
                    rn[rh][1] = pack2(-mean * rs, -mean * rs);
                }
            }
            float acc[32];
            auto ln2_half = [&](auto HC) {
                constexpr int st = decltype(HC)::value;
                uint4 v[4][4];
                landed_read<st>(v, land, land_x, scr->x2 + (size_t)tile * 4096 + t, tag);
                if (st == 1 && lane == 0) mbar_arrive(BAR(R_Y0) + 8 * w);
                uint32_t cw[28], sw[28];
#pragma unroll
                for (int s = 0; s < 4; s++) {
                    uint32_t rr[14];
                    unpack14(v[s], rr);
#pragma unroll
                    for (int i = 0; i < 7; i++) {
                        const int blk = 7 * s + i;
                        if ((blk & 3) == 0) {
                            const uint32_t o = (7 * st + (blk >> 2)) * 64 + q * 16;
                            const uint4 c4 = lds128(SB + OFF_C2 + o), s4 = lds128(SB + OFF_S2 + o);
                            cw[blk] = c4.x; cw[blk + 1] = c4.y; cw[blk + 2] = c4.z; cw[blk + 3] = c4.w;
                            sw[blk] = s4.x; sw[blk + 1] = s4.y; sw[blk + 2] = s4.z; sw[blk + 3] = s4.w;
                        }
                        const int ks = 14 * st + 7 * (s >> 1) + (i == 6 ? 6 : 3 * (s & 1) + (i >> 1));
                        const int hi = i == 6 ? (s & 1) : (i & 1);
                        af[ks][2 * hi] = hfma2(hfma2(rr[2 * i], rn[0][0], rn[0][1]), cw[blk], sw[blk]);
                        af[ks][2 * hi + 1] = hfma2(hfma2(rr[2 * i + 1], rn[1][0], rn[1][1]), cw[blk], sw[blk]);
                    }
                }
#pragma unroll
                for (int s = 0; s < 14; s++) pin(af[14 * st + s]);
                constexpr int n = N_GU3 + st;
                mbar_wait(BAR(F_RING + n % NSLOT), (n / NSLOT) & 1);
                WG_FENCE();
#pragma unroll
                for (int s = 0; s < 14; s++)
                    wgmma_n64_t1(acc, af[14 * st + s],
                                 mk_desc(SLOTA(ring_slot(n % NSLOT)) + ((s / 7) * 14 + kstep_group<6>(s % 7)) * 512, SLOT / 2,
                                         512 * kstep_gap(s % 7), 2),
                                 (st | s) != 0);
                WG_COMMIT();
            };
            ln2_half(IC<0>{});
            TS(8);
            ln2_half(IC<1>{});
            WG_WAIT(1);
            if (lane == 0) mbar_arrive(BAR(E_RING + N_GU3 % NSLOT));
            WG_WAIT(0);
            pin(acc);
            if (lane == 0) mbar_arrive(BAR(E_RING + (N_GU3 + 1) % NSLOT));
            uint32_t hp[8];
#pragma unroll
            for (int i = 0; i < 8; i++) hp[i] = pack2(fmaxf(acc[2 * i], 0.f) * acc[16 + 2 * i], fmaxf(acc[2 * i + 1], 0.f) * acc[17 + 2 * i]);
            sts128(hs + 4 * 2048, hp[0], hp[1], hp[2], hp[3]);
            sts128(hs + 5 * 2048, hp[4], hp[5], hp[6], hp[7]);
            st_rlx128(hout + 15 * 128, hp[0], hp[1], hp[2], prmt(hp[3], tag, 0x1054));
            st_rlx128(hout + 16 * 128, hp[4], hp[5], hp[6], prmt(hp[7], tag, 0x1054));
            st_rlx128(hout + 17 * 128, prmt(hp[3], hp[7], 0x7632), 0, 0, tag);
        }
#pragma unroll
        for (int p = 0; p < 3; p++) {
            float acc[64];
#pragma unroll
            for (int st = 0; st < 4; st++) {
                const int n = N_GU + 4 * p + st;
                mbar_wait(BAR(F_RING + n % NSLOT), (n / NSLOT) & 1);
                WG_FENCE();
#pragma unroll
                for (int s = 0; s < 7; s++)
                    wgmma_n128_t1(acc, af[7 * st + s],
                                  mk_desc(SLOTA(ring_slot(n % NSLOT)) + kstep_group<6>(s) * 1024, SLOT / 2, 1024 * kstep_gap(s), 1),
                                  (st | s) != 0);
                WG_COMMIT();
                if (st > 0) {
                    WG_WAIT(1);
                    if (lane == 0) mbar_arrive(BAR(E_RING + (n - 1) % NSLOT));
                }
            }
            WG_WAIT(0);
            pin(acc);
            if (lane == 0) mbar_arrive(BAR(E_RING + (N_GU + 4 * p + 3) % NSLOT));
#pragma unroll
            for (int i = 0; i < 16; i++)
                hh[4 * p + (i >> 2)][i & 3] = pack2(fmaxf(acc[2 * i], 0.f) * acc[32 + 2 * i], fmaxf(acc[2 * i + 1], 0.f) * acc[33 + 2 * i]);
#pragma unroll
            for (int k = 0; k < 4; k++)
                st_rlx128(hout + (5 * p + k) * 128, hh[4 * p + k][0], hh[4 * p + k][1], hh[4 * p + k][2], prmt(hh[4 * p + k][3], tag, 0x1054));
            st_rlx128(hout + (5 * p + 4) * 128, prmt(hh[4 * p][3], hh[4 * p + 1][3], 0x7632), prmt(hh[4 * p + 2][3], hh[4 * p + 3][3], 0x7632),
                      0, tag);
            if (p == 0) {
#pragma unroll
                for (int k = 0; k < 4; k++) sts128(hs + k * 2048, hh[k][0], hh[k][1], hh[k][2], hh[k][3]);
            }
        }
#pragma unroll
        for (int k = 0; k < 6; k++) {
            const uint4 hv = lds128(hs + k * 2048);
            const int ks = k < 4 ? k : k + 8;
            hh[ks][0] = hv.x; hh[ks][1] = hv.y; hh[ks][2] = hv.z; hh[ks][3] = hv.w;
        }
#pragma unroll
        for (int s = 0; s < 14; s++) pin(hh[s]);
        TS(9);

        const uint32_t ob = jo + jo * 256, os = jo + (jo ? (uint32_t)-1536 : 0u);
        const uint32_t pbg = jo + (1 - jo) * 256, psm = jo + (jo ? 0u : (uint32_t)-1536);
        float accD[2][28], sum[28];
        const uint4* pin_base = scr->part + ((size_t)tile * 8 + j) * 2048 + t;
        uint4* pout_base = scr->part + (size_t)tile * 8 * 2048 + t;
        uint4 xv[4], pv[2][4], hv[18];
        const uint4* hin = scr->hx + ((size_t)tile * 8 + (j ^ 1)) * 18 * 128 + t;
#pragma unroll
        for (int k = 0; k < 18; k++) hv[k] = ld_rlx128(hin + k * 128);
        auto load_part = [&](uint4 (&v)[4], int k) {
#pragma unroll
            for (int i = 0; i < 4; i++) v[i] = ld_rlx128(pin_base + k * 512 + i * 128);
        };
        auto add_part = [&](uint4 (&v)[4], int k) {
            int it = 0;
#pragma unroll 1
            while (__builtin_expect(__any_sync(0xFFFFFFFFu, tag_bad(v, tag) != 0), 0)) {
                load_part(v, k);
                if (++it > SPIN_LIMIT) break;
            }
            uint32_t rr[14];
            unpack14(v, rr);
#pragma unroll
            for (int i = 0; i < 14; i++) {
                sum[2 * i] += bf_lo(rr[i]);
                sum[2 * i + 1] += bf_hi(rr[i]);
            }
        };
        auto issue_pass = [&](float (&acc)[28], uint32_t (&a)[14][4], auto MC) {
            constexpr int m = decltype(MC)::value, pos = m == 7 ? 0 : m, par = (0xAC >> m) & 1;
            mbar_wait(BAR(F_RING + pos), m == 7);
            WG_FENCE();
#pragma unroll
            for (int s = 0; s < 14; s++)
                wgmma_n56_t1(acc, a[s], mk_desc16(par ? (s < 12 ? pbg : psm) : (s < 12 ? ob : os), SLOTA(ring_slot(pos)) + s * 2048, 0, 1024, 1),
                             par || s != 0);
            WG_COMMIT();
        };
        auto send = [&](float (&acc)[28], int k) {
            pin(acc);
            uint32_t pb[14];
#pragma unroll
            for (int i = 0; i < 14; i++) pb[i] = pack2(acc[2 * i], acc[2 * i + 1]);
            publish14(pout_base + ((j + 2 * k + 2) & 7) * 2048 + k * 512, pb, tag);
        };
        issue_pass(accD[0], hh, IC<0>{});
        issue_pass(accD[1], hh, IC<1>{});
        WG_WAIT(1);
        if (lane == 0) mbar_arrive(BAR(E_RING));
        uint32_t hp[14][4];
        {
            int it = 0;
#pragma unroll 1
            while (true) {
                uint32_t bad = 0;
#pragma unroll
                for (int k = 0; k < 18; k++) bad |= hv[k].w ^ tag;
                if (!__any_sync(0xFFFFFFFFu, (bad & 0xFFFFu) != 0) || ++it > SPIN_LIMIT) break;
#pragma unroll
                for (int k = 0; k < 18; k++) hv[k] = ld_rlx128(hin + k * 128);
            }
#pragma unroll
            for (int s = 0; s < 14; s++) {
                const int vi = s < 12 ? 5 * (s >> 2) + (s & 3) : 15 + (s - 12), xi = s < 12 ? 5 * (s >> 2) + 4 : 17;
                hp[s][0] = hv[vi].x; hp[s][1] = hv[vi].y; hp[s][2] = hv[vi].z;
                hp[s][3] = prmt(hv[vi].w, (s & 2) && s < 12 ? hv[xi].y : hv[xi].x, (s & 1) ? 0x7632 : 0x5432);
                pin(hp[s]);
            }
        }
        TS(27);
        {
            const uint4* src = scr->x2 + ((size_t)tile * 8 + j) * 512 + t;
#pragma unroll
            for (int k = 0; k < 4; k++) xv[k] = ld_rlx128(src + k * 128);
        }
        issue_pass(accD[0], hp, IC<2>{});
        issue_pass(accD[1], hp, IC<3>{});
        WG_WAIT(1);
        send(accD[0], 0);
        issue_pass(accD[0], hh, IC<4>{});
        WG_WAIT(1);
        send(accD[1], 1);
        issue_pass(accD[0], hp, IC<5>{});
        issue_pass(accD[1], hh, IC<6>{});
        WG_WAIT(1);
        send(accD[0], 2);
        load_part(pv[0], 0);
        load_part(pv[1], 1);
        issue_pass(accD[1], hp, IC<7>{});
        TS(10);
#pragma unroll
        for (int i = 0; i < 28; i++) sum[i] = 0.f;
        add_part(pv[0], 0);
        load_part(pv[0], 2);
        add_part(pv[1], 1);
        WG_WAIT(0);
        pin(accD[1]);
#pragma unroll
        for (int i = 0; i < 28; i++) sum[i] += accD[1][i];
        add_part(pv[0], 2);
        {
            uint32_t rr[14];
            unpack14(xv, rr);
#pragma unroll
            for (int i = 0; i < 7; i++) {
                const uint32_t g = lds32(SB + OFF_GB + (4 * i + q) * 4);
                const float o0 = fmaf(bf_lo(g), sum[4 * i], bf_lo(rr[2 * i]));
                const float o1 = fmaf(bf_hi(g), sum[4 * i + 1], bf_hi(rr[2 * i]));
                const float o2 = fmaf(bf_lo(g), sum[4 * i + 2], bf_lo(rr[2 * i + 1]));
                const float o3 = fmaf(bf_hi(g), sum[4 * i + 3], bf_hi(rr[2 * i + 1]));
                *(uint32_t*)(out + (size_t)row0 * DM + 56 * j + 8 * i + 2 * q) = pack2(o0, o1);
                *(uint32_t*)(out + (size_t)(row0 + 8) * DM + 56 * j + 8 * i + 2 * q) = pack2(o2, o3);
            }
        }
        if (tid < 32) scr->epoch[bid * 32 + lane] = tag;
        TS(11);
        TG(31);
    }
}

typedef CUresult (*EncodeFn)(CUtensorMap*, CUtensorMapDataType, cuuint32_t, void*, const cuuint64_t*, const cuuint64_t*,
                             const cuuint32_t*, const cuuint32_t*, CUtensorMapInterleave, CUtensorMapSwizzle,
                             CUtensorMapL2promotion, CUtensorMapFloatOOBfill);

void make_map_2d(EncodeFn enc, CUtensorMap* m, const void* ptr, uint64_t cols, uint64_t rows, uint32_t bc, uint32_t br,
                 CUtensorMapSwizzle swz) {
    cuuint64_t dims[2] = {cols, rows};
    cuuint64_t strides[1] = {cols * 2};
    cuuint32_t box[2] = {bc, br};
    cuuint32_t es[2] = {1, 1};
    enc(m, CU_TENSOR_MAP_DATA_TYPE_BFLOAT16, 2, const_cast<void*>(ptr), dims, strides, box, es, CU_TENSOR_MAP_INTERLEAVE_NONE, swz,
        CU_TENSOR_MAP_L2_PROMOTION_L2_128B, CU_TENSOR_MAP_FLOAT_OOB_FILL_NONE);
}

}

extern "C" void kernel_launch(void* const* d_in, const int* in_sizes, int n_in, void* d_out, int out_size) {
    (void)in_sizes; (void)n_in; (void)out_size;
    const __nv_bfloat16* x = (const __nv_bfloat16*)d_in[0];
    const __nv_bfloat16* wqkv = (const __nv_bfloat16*)d_in[1];
    const __nv_bfloat16* wo = (const __nv_bfloat16*)d_in[2];
    const __nv_bfloat16* wg = (const __nv_bfloat16*)d_in[4];
    const __nv_bfloat16* wu = (const __nv_bfloat16*)d_in[5];
    const __nv_bfloat16* wd = (const __nv_bfloat16*)d_in[6];
    const __nv_bfloat16* cv = (const __nv_bfloat16*)d_in[7];
    const __nv_bfloat16* wm = (const __nv_bfloat16*)d_in[8];

    void* fn = nullptr;
    cudaDriverEntryPointQueryResult qr;
    cudaGetDriverEntryPoint("cuTensorMapEncodeTiled", &fn, cudaEnableDefault, &qr);
    EncodeFn enc = (EncodeFn)fn;

    CUtensorMap tx, tq, two, tg, tu, tg3, tu3, td, tmm;
    make_map_2d(enc, &tmm, wm, 6 * DM, DM, 16, 224, CU_TENSOR_MAP_SWIZZLE_NONE);
    make_map_2d(enc, &tx, x, DM, SEQ, 64, 128, CU_TENSOR_MAP_SWIZZLE_128B);
    make_map_2d(enc, &tq, wqkv, 3 * DM, DM, 64, 224, CU_TENSOR_MAP_SWIZZLE_128B);
    make_map_2d(enc, &two, wo, DM, DM, 64, 224, CU_TENSOR_MAP_SWIZZLE_128B);
    make_map_2d(enc, &tg, wg, FF, DM, 64, 112, CU_TENSOR_MAP_SWIZZLE_128B);
    make_map_2d(enc, &tu, wu, FF, DM, 64, 112, CU_TENSOR_MAP_SWIZZLE_128B);
    make_map_2d(enc, &tg3, wg, FF, DM, 32, 224, CU_TENSOR_MAP_SWIZZLE_64B);
    make_map_2d(enc, &tu3, wu, FF, DM, 32, 224, CU_TENSOR_MAP_SWIZZLE_64B);
    make_map_2d(enc, &td, wd, DM, FF, 64, 224, CU_TENSOR_MAP_SWIZZLE_128B);

    cudaFuncSetAttribute(fused_block_kernel, cudaFuncAttributeMaxDynamicSharedMemorySize, SMEM_BYTES);
    void* scr = nullptr;
    cudaGetSymbolAddress(&scr, g_scr);
    fused_block_kernel<<<NCTA, NTHREADS, SMEM_BYTES>>>((Scratch*)scr, x, cv, wm, (__nv_bfloat16*)d_out, wqkv, wo, wg, wu, wd, tx, tq, two, tg,
                                                       tu, tg3, tu3, td, tmm);
}
```

```cpp
#include <cuda_runtime.h>
#include <cuda_bf16.h>
#include <cuda.h>
#include <stdint.h>

#define DBG_TIMING 0

namespace {

constexpr int SEQ = 2048, DM = 448, FF = 1792;
constexpr int NCTA = 128;
constexpr int NTHREADS = 384;
constexpr uint32_t SLOT = 28672;
constexpr int NSLOT = 7;
constexpr uint32_t KVT = 7168;
constexpr uint32_t OFF_QX = NSLOT * SLOT;
constexpr uint32_t OFF_C1 = OFF_QX + 24576;
constexpr uint32_t OFF_S1 = OFF_C1 + 896;
constexpr uint32_t OFF_C2 = OFF_S1 + 896;
constexpr uint32_t OFF_S2 = OFF_C2 + 896;
constexpr uint32_t OFF_GA = OFF_S2 + 896;
constexpr uint32_t OFF_GB = OFF_GA + 128;
constexpr uint32_t OFF_RED = OFF_GB + 128;
constexpr uint32_t OFF_BAR = OFF_RED + 1024;
constexpr int NRING = 5;
enum { F_X0, F_K0 = F_X0 + 3, F_K1, F_V0, F_V1, F_Q0, F_Q1, F_WO0, F_WO1, F_HK, F_HV, F_O0, F_O1, F_Y0, F_Y1, F_S0, F_S1, F_R0, F_R1, F_MOD2, F_WM, R_WM,
       F_H0, F_H1, R_PR, F_P, F_RING = F_P + 8,
       N_ONE = F_RING + NRING,
       R_X = N_ONE, R_K, R_V, R_Q, R_ATT, R_WO, R_KST, R_VST, E_RING,
       N_EIGHT = E_RING + NRING,
       R_O0 = N_EIGHT, R_O1, R_Y0, R_Y1, R_H0, R_H1, R_XR, N_BARS };
constexpr uint32_t SMEM_BYTES = OFF_BAR + 8 * N_BARS;
constexpr uint32_t SB = 0x400;
__host__ __device__ constexpr uint32_t BAR(int i) { return SB + OFF_BAR + 8 * i; }
__host__ __device__ constexpr uint32_t SLOTA(int i) { return SB + i * SLOT; }
__host__ __device__ constexpr int ring_slot(int i) { return i == 0 ? 6 : i + 1; }
constexpr int N_ITEMS = 22;

constexpr int SPIN_LIMIT = 1 << 17;

struct Scratch {
    uint4 part[32 * 8 * 4 * 4 * 128];
    uint4 o[32 * 8 * 4 * 128];
    uint4 x2[32 * 8 * 4 * 128];
    uint2 st2[32 * 8 * 64];
    uint8_t kv[16 * 8 * 2 * 2 * KVT];
    uint4 modp[4 * 4 * 224];
    uint2 mod[1344];
    uint2 hint[(2 * 32 + 32 * 8) * 64];
    uint32_t kvflag[16 * 8 * 2 * 8];
    uint32_t epoch[NCTA * 32];
};
__device__ __align__(1024) Scratch g_scr;

__device__ __forceinline__ uint32_t smem_u32(const void* p) { return (uint32_t)__cvta_generic_to_shared(p); }
__device__ __forceinline__ uint32_t cta_win() { return (blockIdx.x & 1u) << 24; }
__device__ __forceinline__ void mbar_init(uint32_t bar, uint32_t cnt) { bar += cta_win();
    asm volatile("mbarrier.init.shared::cta.b64 [%0], %1;" ::"r"(bar), "r"(cnt) : "memory");
}
__device__ __forceinline__ void mbar_arrive(uint32_t bar) { bar += cta_win();
    asm volatile("mbarrier.arrive.shared::cta.b64 _, [%0];" ::"r"(bar) : "memory");
}
__device__ __forceinline__ void st_async128(uint32_t dst, uint32_t bar, uint32_t x, uint32_t y, uint32_t z, uint32_t w) {
    asm volatile("st.async.shared::cluster.mbarrier::complete_tx::bytes.v4.u32 [%0], {%2,%3,%4,%5}, [%1];"
                 ::"r"(dst), "r"(bar), "r"(x), "r"(y), "r"(z), "r"(w) : "memory");
}
__device__ __forceinline__ void mbar_wait_cluster(uint32_t bar, uint32_t parity) { bar += cta_win();
    uint32_t done;
    int it = 0;
#pragma unroll 1
    do {
        asm volatile("{\n.reg .pred p;\nmbarrier.try_wait.parity.acquire.cluster.shared::cta.b64 p, [%1], %2;\nselp.u32 %0, 1, 0, p;\n}\n"
                     : "=r"(done) : "r"(bar), "r"(parity) : "memory");
        if (++it > SPIN_LIMIT) break;
    } while (!done);
}
__device__ __forceinline__ void mbar_expect_tx(uint32_t bar, uint32_t bytes) { bar += cta_win();
    asm volatile("mbarrier.arrive.expect_tx.shared::cta.b64 _, [%0], %1;" ::"r"(bar), "r"(bytes) : "memory");
}
__device__ __forceinline__ void mbar_wait(uint32_t bar, uint32_t parity) { bar += cta_win();
    uint32_t done;
    int it = 0;
#pragma unroll 1
    do {
        asm volatile("{\n.reg .pred p;\nmbarrier.try_wait.parity.shared::cta.b64 p, [%1], %2;\nselp.u32 %0, 1, 0, p;\n}\n"
                     : "=r"(done) : "r"(bar), "r"(parity) : "memory");
        if (++it > SPIN_LIMIT) break;
    } while (!done);
}
__device__ __forceinline__ void tma_2d_e(uint32_t dst, const CUtensorMap* m, int c0, int c1, uint32_t bar) {
    dst += cta_win(); bar += cta_win();
    asm volatile("{\n.reg .pred p;\nelect.sync _|p, 0xffffffff;\n"
                 "@p cp.async.bulk.tensor.2d.shared::cluster.global.mbarrier::complete_tx::bytes [%0], [%1, {%3, %4}], [%2];\n}\n"
                 ::"r"(dst), "l"(m), "r"(bar), "r"(c0), "r"(c1) : "memory");
}
__device__ __forceinline__ void expect_tx_e(uint32_t bar, uint32_t bytes) {
    bar += cta_win();
    asm volatile("{\n.reg .pred p;\nelect.sync _|p, 0xffffffff;\n@p mbarrier.arrive.expect_tx.shared::cta.b64 _, [%0], %1;\n}\n"
                 ::"r"(bar), "r"(bytes) : "memory");
}
__device__ __forceinline__ void bulk_g2s(uint32_t dst, const void* src, uint32_t bytes, uint32_t bar) {
    dst += cta_win(); bar += cta_win();
    asm volatile("cp.async.bulk.shared::cluster.global.mbarrier::complete_tx::bytes [%0], [%1], %2, [%3];"
                 ::"r"(dst), "l"(src), "r"(bytes), "r"(bar) : "memory");
}
__device__ __forceinline__ void l2_prefetch(const void* src, uint32_t bytes) {
    asm volatile("cp.async.bulk.prefetch.L2.global [%0], %1;" ::"l"(src), "r"(bytes) : "memory");
}
__device__ __forceinline__ uint4 ld_rlx128(const uint4* p) {
    uint4 v;
    asm volatile("ld.relaxed.gpu.global.v4.u32 {%0,%1,%2,%3}, [%4];" : "=r"(v.x), "=r"(v.y), "=r"(v.z), "=r"(v.w) : "l"(p) : "memory");
    return v;
}
__device__ __forceinline__ void st_rlx128(uint4* p, uint32_t x, uint32_t y, uint32_t z, uint32_t w) {
    asm volatile("st.relaxed.gpu.global.v4.u32 [%0], {%1,%2,%3,%4};" ::"l"(p), "r"(x), "r"(y), "r"(z), "r"(w) : "memory");
}
__device__ __forceinline__ uint2 ld_rlx64(const uint2* p) {
    uint2 v;
    asm volatile("ld.relaxed.gpu.global.v2.u32 {%0,%1}, [%2];" : "=r"(v.x), "=r"(v.y) : "l"(p) : "memory");
    return v;
}
__device__ __forceinline__ void st_rlx64(uint2* p, uint32_t x, uint32_t y) {
    asm volatile("st.relaxed.gpu.global.v2.u32 [%0], {%1,%2};" ::"l"(p), "r"(x), "r"(y) : "memory");
}
__device__ __forceinline__ void st_rlx32(void* p, uint32_t x) {
    asm volatile("st.relaxed.gpu.global.u32 [%0], %1;" ::"l"(p), "r"(x) : "memory");
}
__device__ __forceinline__ uint4 ldg128(const void* p) {
    uint4 v;
    asm volatile("ld.global.nc.L1::no_allocate.v4.u32 {%0,%1,%2,%3}, [%4];" : "=r"(v.x), "=r"(v.y), "=r"(v.z), "=r"(v.w) : "l"(p));
    return v;
}
__device__ __forceinline__ uint4 lds128(uint32_t a) { a += cta_win();
    uint4 v;
    asm volatile("ld.shared.v4.u32 {%0,%1,%2,%3}, [%4];" : "=r"(v.x), "=r"(v.y), "=r"(v.z), "=r"(v.w) : "r"(a) : "memory");
    return v;
}
__device__ __forceinline__ uint32_t lds32(uint32_t a) { a += cta_win();
    uint32_t v;
    asm volatile("ld.shared.u32 %0, [%1];" : "=r"(v) : "r"(a) : "memory");
    return v;
}
__device__ __forceinline__ void sts128(uint32_t a, uint32_t x, uint32_t y, uint32_t z, uint32_t w) { a += cta_win();
    asm volatile("st.shared.v4.u32 [%0], {%1,%2,%3,%4};" ::"r"(a), "r"(x), "r"(y), "r"(z), "r"(w) : "memory");
}
__device__ __forceinline__ void sts32(uint32_t a, uint32_t x) { a += cta_win(); asm volatile("st.shared.u32 [%0], %1;" ::"r"(a), "r"(x) : "memory"); }
__device__ __forceinline__ void stsm4(uint32_t a, uint32_t r0, uint32_t r1, uint32_t r2, uint32_t r3) { a += cta_win();
    asm volatile("stmatrix.sync.aligned.m8n8.x4.shared.b16 [%0], {%1,%2,%3,%4};" ::"r"(a), "r"(r0), "r"(r1), "r"(r2), "r"(r3) : "memory");
}
__device__ __forceinline__ void stsm2(uint32_t a, uint32_t r0, uint32_t r1) { a += cta_win();
    asm volatile("stmatrix.sync.aligned.m8n8.x2.shared.b16 [%0], {%1,%2};" ::"r"(a), "r"(r0), "r"(r1) : "memory");
}
__device__ __forceinline__ void ldsm4(uint32_t (&r)[4], uint32_t a) { a += cta_win();
    asm volatile("ldmatrix.sync.aligned.m8n8.x4.shared.b16 {%0,%1,%2,%3}, [%4];"
                 : "=r"(r[0]), "=r"(r[1]), "=r"(r[2]), "=r"(r[3]) : "r"(a) : "memory");
}
__device__ __forceinline__ void ldsm2(uint32_t& r0, uint32_t& r1, uint32_t a) {
    a += cta_win();
    asm volatile("ldmatrix.sync.aligned.m8n8.x2.shared.b16 {%0,%1}, [%2];" : "=r"(r0), "=r"(r1) : "r"(a) : "memory");
}
__device__ __forceinline__ void hmma8(float (&c)[4], uint32_t a0, uint32_t a1, uint32_t b0) {
    asm volatile("mma.sync.aligned.m16n8k8.row.col.f32.bf16.bf16.f32 {%0,%1,%2,%3}, {%4,%5}, {%6}, {%0,%1,%2,%3};"
                 : "+f"(c[0]), "+f"(c[1]), "+f"(c[2]), "+f"(c[3]) : "r"(a0), "r"(a1), "r"(b0));
}
__device__ __forceinline__ void hmma(float (&c)[4], const uint32_t (&a)[4], uint32_t b0, uint32_t b1) {
    asm volatile("mma.sync.aligned.m16n8k16.row.col.f32.bf16.bf16.f32 {%0,%1,%2,%3}, {%4,%5,%6,%7}, {%8,%9}, {%0,%1,%2,%3};"
                 : "+f"(c[0]), "+f"(c[1]), "+f"(c[2]), "+f"(c[3])
                 : "r"(a[0]), "r"(a[1]), "r"(a[2]), "r"(a[3]), "r"(b0), "r"(b1));
}
__device__ __forceinline__ uint32_t ld_acq32(const void* p) {
    uint32_t v;
    asm volatile("ld.acquire.gpu.global.u32 %0, [%1];" : "=r"(v) : "l"(p) : "memory");
    return v;
}
__device__ __forceinline__ uint32_t ld_rlx32(const void* p) {
    uint32_t v;
    asm volatile("ld.relaxed.gpu.global.u32 %0, [%1];" : "=r"(v) : "l"(p) : "memory");
    return v;
}
__device__ __forceinline__ uint32_t pack2(float lo, float hi) {
    uint32_t r;
    asm("cvt.rn.bf16x2.f32 %0, %1, %2;" : "=r"(r) : "f"(hi), "f"(lo));
    return r;
}
__device__ __forceinline__ float bf_lo(uint32_t v) { return __uint_as_float(v << 16); }
__device__ __forceinline__ float bf_hi(uint32_t v) { return __uint_as_float(v & 0xFFFF0000u); }
__device__ __forceinline__ uint32_t hfma2(uint32_t a, uint32_t b, uint32_t c) {
    uint32_t r;
    asm("fma.rn.bf16x2 %0, %1, %2, %3;" : "=r"(r) : "r"(a), "r"(b), "r"(c));
    return r;
}
__device__ __forceinline__ uint32_t prmt(uint32_t a, uint32_t b, uint32_t sel) {
    uint32_t r;
    asm("prmt.b32 %0, %1, %2, %3;" : "=r"(r) : "r"(a), "r"(b), "r"(sel));
    return r;
}
__device__ __forceinline__ float ex2f(float x) {
    float r;
    asm("ex2.approx.ftz.f32 %0, %1;" : "=f"(r) : "f"(x));
    return r;
}
__device__ __forceinline__ uint32_t reglu2(float g0, float g1, float u0, float u1) {
    uint32_t g, r;
    asm("cvt.rn.relu.bf16x2.f32 %0, %1, %2;" : "=r"(g) : "f"(g1), "f"(g0));
    asm("mul.rn.bf16x2 %0, %1, %2;" : "=r"(r) : "r"(g), "r"(pack2(u0, u1)));
    return r;
}
__device__ __forceinline__ float silu_bf(float v) {
    float s = __fdividef(v, 1.0f + __expf(-v));
    return bf_lo(pack2(s, 0.f));
}
__device__ __forceinline__ void bar_sync(int id, int n) { asm volatile("bar.sync %0, %1;" ::"r"(id), "r"(n) : "memory"); }
__device__ __forceinline__ void bar_arrive(int id, int n) { asm volatile("bar.arrive %0, %1;" ::"r"(id), "r"(n) : "memory"); }
__device__ __forceinline__ void fence_async_smem() { asm volatile("fence.proxy.async.shared::cta;" ::: "memory"); }
__device__ __forceinline__ uint64_t mk_desc16(uint32_t a16, uint32_t off, uint32_t lbo, uint32_t sbo, uint32_t swz) {
    const uint32_t lo = a16 + ((off >> 4) + ((lbo >> 4) << 16));
    const uint32_t hi = (sbo >> 4) | (swz << 30);
    return ((uint64_t)hi << 32) | lo;
}
#define WG_FENCE() asm volatile("wgmma.fence.sync.aligned;" ::: "memory")
#define WG_COMMIT() asm volatile("wgmma.commit_group.sync.aligned;" ::: "memory")
#define WG_WAIT(n) asm volatile("wgmma.wait_group.sync.aligned %0;" ::"n"(n) : "memory")
template <int N> __device__ __forceinline__ void pin(float (&d)[N]) {
#pragma unroll
    for (int i = 0; i < N; i++) asm volatile("" : "+f"(d[i])::"memory");
}
__device__ __forceinline__ void pin(uint32_t (&a)[2], uint32_t (&b)[2]) {
    asm volatile("" : "+r"(a[0]), "+r"(a[1]), "+r"(b[0]), "+r"(b[1])::"memory");
}
__device__ __forceinline__ void pin(uint32_t (&a)[4]) {
    asm volatile("" : "+r"(a[0]), "+r"(a[1]), "+r"(a[2]), "+r"(a[3])::"memory");
}

__device__ __forceinline__ void wgmma_n32_t1(float (&d)[16], const uint32_t (&a)[4], uint64_t descB, int scaleD) {
    asm volatile("{\n.reg .pred p;\nsetp.ne.b32 p, %21, 0;\n"
        "wgmma.mma_async.sync.aligned.m64n32k16.f32.bf16.bf16 "
        "{%0, %1, %2, %3, %4, %5, %6, %7, %8, %9, %10, %11, %12, %13, %14, %15}, "
        "{%16, %17, %18, %19}, %20, p, 1, 1, 1;\n}\n"
        : "+f"(d[0]), "+f"(d[1]), "+f"(d[2]), "+f"(d[3]), "+f"(d[4]), "+f"(d[5]), "+f"(d[6]), "+f"(d[7]),
          "+f"(d[8]), "+f"(d[9]), "+f"(d[10]), "+f"(d[11]), "+f"(d[12]), "+f"(d[13]), "+f"(d[14]), "+f"(d[15])
        : "r"(a[0]), "r"(a[1]), "r"(a[2]), "r"(a[3]), "l"(descB), "r"(scaleD));
}
__device__ __forceinline__ void wgmma_n56_t1(float (&d)[28], const uint32_t (&a)[4], uint64_t descB, int scaleD) {
    asm volatile("{\n.reg .pred p;\nsetp.ne.b32 p, %33, 0;\n"
        "wgmma.mma_async.sync.aligned.m64n56k16.f32.bf16.bf16 "
        "{%0, %1, %2, %3, %4, %5, %6, %7, %8, %9, %10, %11, %12, %13, %14, %15, "
        "%16, %17, %18, %19, %20, %21, %22, %23, %24, %25, %26, %27}, "
        "{%28, %29, %30, %31}, %32, p, 1, 1, 1;\n}\n"
        : "+f"(d[0]), "+f"(d[1]), "+f"(d[2]), "+f"(d[3]), "+f"(d[4]), "+f"(d[5]), "+f"(d[6]), "+f"(d[7]),
          "+f"(d[8]), "+f"(d[9]), "+f"(d[10]), "+f"(d[11]), "+f"(d[12]), "+f"(d[13]), "+f"(d[14]), "+f"(d[15]),
          "+f"(d[16]), "+f"(d[17]), "+f"(d[18]), "+f"(d[19]), "+f"(d[20]), "+f"(d[21]), "+f"(d[22]), "+f"(d[23]),
          "+f"(d[24]), "+f"(d[25]), "+f"(d[26]), "+f"(d[27])
        : "r"(a[0]), "r"(a[1]), "r"(a[2]), "r"(a[3]), "l"(descB), "r"(scaleD));
}
__device__ __forceinline__ void wgmma_n64_t0(float (&d)[32], const uint32_t (&a)[4], uint64_t descB, int scaleD) {
    asm volatile("{\n.reg .pred p;\nsetp.ne.b32 p, %37, 0;\n"
        "wgmma.mma_async.sync.aligned.m64n64k16.f32.bf16.bf16 "
        "{%0, %1, %2, %3, %4, %5, %6, %7, %8, %9, %10, %11, %12, %13, %14, %15, "
        "%16, %17, %18, %19, %20, %21, %22, %23, %24, %25, %26, %27, %28, %29, %30, %31}, "
        "{%32, %33, %34, %35}, %36, p, 1, 1, 0;\n}\n"
        : "+f"(d[0]), "+f"(d[1]), "+f"(d[2]), "+f"(d[3]), "+f"(d[4]), "+f"(d[5]), "+f"(d[6]), "+f"(d[7]),
          "+f"(d[8]), "+f"(d[9]), "+f"(d[10]), "+f"(d[11]), "+f"(d[12]), "+f"(d[13]), "+f"(d[14]), "+f"(d[15]),
          "+f"(d[16]), "+f"(d[17]), "+f"(d[18]), "+f"(d[19]), "+f"(d[20]), "+f"(d[21]), "+f"(d[22]), "+f"(d[23]),
          "+f"(d[24]), "+f"(d[25]), "+f"(d[26]), "+f"(d[27]), "+f"(d[28]), "+f"(d[29]), "+f"(d[30]), "+f"(d[31])
        : "r"(a[0]), "r"(a[1]), "r"(a[2]), "r"(a[3]), "l"(descB), "r"(scaleD));
}
__device__ __forceinline__ void wgmma_n64_t1(float (&d)[32], const uint32_t (&a)[4], uint64_t descB, int scaleD) {
    asm volatile("{\n.reg .pred p;\nsetp.ne.b32 p, %37, 0;\n"
        "wgmma.mma_async.sync.aligned.m64n64k16.f32.bf16.bf16 "
        "{%0, %1, %2, %3, %4, %5, %6, %7, %8, %9, %10, %11, %12, %13, %14, %15, "
        "%16, %17, %18, %19, %20, %21, %22, %23, %24, %25, %26, %27, %28, %29, %30, %31}, "
        "{%32, %33, %34, %35}, %36, p, 1, 1, 1;\n}\n"
        : "+f"(d[0]), "+f"(d[1]), "+f"(d[2]), "+f"(d[3]), "+f"(d[4]), "+f"(d[5]), "+f"(d[6]), "+f"(d[7]),
          "+f"(d[8]), "+f"(d[9]), "+f"(d[10]), "+f"(d[11]), "+f"(d[12]), "+f"(d[13]), "+f"(d[14]), "+f"(d[15]),
          "+f"(d[16]), "+f"(d[17]), "+f"(d[18]), "+f"(d[19]), "+f"(d[20]), "+f"(d[21]), "+f"(d[22]), "+f"(d[23]),
          "+f"(d[24]), "+f"(d[25]), "+f"(d[26]), "+f"(d[27]), "+f"(d[28]), "+f"(d[29]), "+f"(d[30]), "+f"(d[31])
        : "r"(a[0]), "r"(a[1]), "r"(a[2]), "r"(a[3]), "l"(descB), "r"(scaleD));
}
__device__ __forceinline__ void wgmma_n128_t1(float (&d)[64], const uint32_t (&a)[4], uint64_t descB, int scaleD) {
    asm volatile("{\n.reg .pred p;\nsetp.ne.b32 p, %69, 0;\n"
        "wgmma.mma_async.sync.aligned.m64n128k16.f32.bf16.bf16 "
        "{%0, %1, %2, %3, %4, %5, %6, %7, %8, %9, %10, %11, %12, %13, %14, %15, "
        "%16, %17, %18, %19, %20, %21, %22, %23, %24, %25, %26, %27, %28, %29, %30, %31, "
        "%32, %33, %34, %35, %36, %37, %38, %39, %40, %41, %42, %43, %44, %45, %46, %47, "
        "%48, %49, %50, %51, %52, %53, %54, %55, %56, %57, %58, %59, %60, %61, %62, %63}, "
        "{%64, %65, %66, %67}, %68, p, 1, 1, 1;\n}\n"
        : "+f"(d[0]), "+f"(d[1]), "+f"(d[2]), "+f"(d[3]), "+f"(d[4]), "+f"(d[5]), "+f"(d[6]), "+f"(d[7]),
          "+f"(d[8]), "+f"(d[9]), "+f"(d[10]), "+f"(d[11]), "+f"(d[12]), "+f"(d[13]), "+f"(d[14]), "+f"(d[15]),
          "+f"(d[16]), "+f"(d[17]), "+f"(d[18]), "+f"(d[19]), "+f"(d[20]), "+f"(d[21]), "+f"(d[22]), "+f"(d[23]),
          "+f"(d[24]), "+f"(d[25]), "+f"(d[26]), "+f"(d[27]), "+f"(d[28]), "+f"(d[29]), "+f"(d[30]), "+f"(d[31]),
          "+f"(d[32]), "+f"(d[33]), "+f"(d[34]), "+f"(d[35]), "+f"(d[36]), "+f"(d[37]), "+f"(d[38]), "+f"(d[39]),
          "+f"(d[40]), "+f"(d[41]), "+f"(d[42]), "+f"(d[43]), "+f"(d[44]), "+f"(d[45]), "+f"(d[46]), "+f"(d[47]),
          "+f"(d[48]), "+f"(d[49]), "+f"(d[50]), "+f"(d[51]), "+f"(d[52]), "+f"(d[53]), "+f"(d[54]), "+f"(d[55]),
          "+f"(d[56]), "+f"(d[57]), "+f"(d[58]), "+f"(d[59]), "+f"(d[60]), "+f"(d[61]), "+f"(d[62]), "+f"(d[63])
        : "r"(a[0]), "r"(a[1]), "r"(a[2]), "r"(a[3]), "l"(descB), "r"(scaleD));
}

#define TSH(k) do {} while (0)
#define TG(k) do {} while (0)
#define TS(k) do {} while (0)

__device__ __forceinline__ void publish14(uint4* dst, const uint32_t (&r)[14], uint32_t tag) {
    st_rlx128(dst + 0 * 128, r[0], r[1], r[2], prmt(r[3], tag, 0x1054));
    st_rlx128(dst + 1 * 128, r[4], r[5], r[6], prmt(r[7], tag, 0x1054));
    st_rlx128(dst + 2 * 128, r[8], r[9], r[10], prmt(r[11], tag, 0x1054));
    st_rlx128(dst + 3 * 128, r[12], r[13], prmt(r[3], r[7], 0x7632), prmt(r[11], tag, 0x3254));
}
__device__ __forceinline__ uint32_t tag_bad(const uint4 (&v)[4], uint32_t tag) {
    return ((v[0].w ^ tag) | (v[1].w ^ tag) | (v[2].w ^ tag) | (v[3].w ^ tag)) & 0xFFFFu;
}
__device__ __forceinline__ void unpack14(const uint4 (&v)[4], uint32_t (&r)[14]) {
    r[0] = v[0].x; r[1] = v[0].y; r[2] = v[0].z; r[3] = prmt(v[0].w, v[3].z, 0x5432);
    r[4] = v[1].x; r[5] = v[1].y; r[6] = v[1].z; r[7] = prmt(v[1].w, v[3].z, 0x7632);
    r[8] = v[2].x; r[9] = v[2].y; r[10] = v[2].z; r[11] = prmt(v[2].w, v[3].w, 0x7632);
    r[12] = v[3].x; r[13] = v[3].y;
}
template <int ODD> __host__ __device__ constexpr int kstep_group(int s) {
    return s == 6 ? ODD : (s / 3) * 7 + 2 * (s % 3) + (2 * (s % 3) >= ODD ? 1 : 0);
}
__host__ __device__ constexpr int kstep_gap(int s) { return s == 6 ? 7 : 1; }
__device__ __forceinline__ float reduce8(float (&a)[8], int lane) {
    {
        bool up = lane & 16;
#pragma unroll
        for (int i = 0; i < 4; i++) {
            float keep = up ? a[i + 4] : a[i], send = up ? a[i] : a[i + 4];
            a[i] = keep + __shfl_xor_sync(0xFFFFFFFFu, send, 16);
        }
    }
    {
        bool up = lane & 8;
#pragma unroll
        for (int i = 0; i < 2; i++) {
            float keep = up ? a[i + 2] : a[i], send = up ? a[i] : a[i + 2];
            a[i] = keep + __shfl_xor_sync(0xFFFFFFFFu, send, 8);
        }
    }
    {
        bool up = lane & 4;
        float keep = up ? a[1] : a[0], send = up ? a[0] : a[1];
        a[0] = keep + __shfl_xor_sync(0xFFFFFFFFu, send, 4);
    }
    return a[0];
}
__device__ __forceinline__ void fma8(float (&a)[8], float s, uint4 w) {
    a[0] = fmaf(s, bf_lo(w.x), a[0]); a[1] = fmaf(s, bf_hi(w.x), a[1]);
    a[2] = fmaf(s, bf_lo(w.y), a[2]); a[3] = fmaf(s, bf_hi(w.y), a[3]);
    a[4] = fmaf(s, bf_lo(w.z), a[4]); a[5] = fmaf(s, bf_hi(w.z), a[5]);
    a[6] = fmaf(s, bf_lo(w.w), a[6]); a[7] = fmaf(s, bf_hi(w.w), a[7]);
}
__device__ __forceinline__ float quad_sum(float v) {
    v += __shfl_xor_sync(0xFFFFFFFFu, v, 1);
    v += __shfl_xor_sync(0xFFFFFFFFu, v, 2);
    return v;
}
__device__ __forceinline__ float quad_max(float v) {
    v = fmaxf(v, __shfl_xor_sync(0xFFFFFFFFu, v, 1));
    v = fmaxf(v, __shfl_xor_sync(0xFFFFFFFFu, v, 2));
    return v;
}
__device__ __forceinline__ void store_kv(uint32_t tile_addr, uint8_t* gdst, const float (&acc)[28], int warp, int lane, uint32_t bar) {
    uint32_t p[14];
#pragma unroll
    for (int i = 0; i < 14; i++) p[i] = pack2(acc[2 * i], acc[2 * i + 1]);
    uint32_t* g = (uint32_t*)(gdst + warp * 256) + lane;
#pragma unroll
    for (int i = 0; i < 14; i++) g[(i >> 1) * 256 + (i & 1) * 32] = p[i];
    __syncwarp();
    if (lane == 0) mbar_arrive(bar);
    uint32_t a = tile_addr + (lane >> 4) * 1024 + (2 * warp + ((lane >> 3) & 1)) * 128 + (lane & 7) * 16;
#pragma unroll
    for (int i = 0; i < 3; i++) stsm4(a + i * 2048, p[4 * i], p[4 * i + 1], p[4 * i + 2], p[4 * i + 3]);
    uint32_t a2 = tile_addr + 6 * 1024 + (2 * warp + ((lane >> 3) & 1)) * 128 + (lane & 7) * 16;
    stsm2(a2, p[12], p[13]);
}

constexpr int NCOPY = 4;
constexpr int HS = 8;
constexpr int NPRE = 2;
constexpr int PV_SPLIT = 1;
template <int V> struct IC { static constexpr int value = V; };

__device__ __noinline__ void refetch(uint32_t main_addr, uint32_t ext_addr, const uint4* src, uint32_t mask) {
#pragma unroll 1
    while (mask) {
        const int s = __ffs(mask) - 1;
        mask &= mask - 1;
        const uint32_t dst = s < 7 ? main_addr + s * 8192 : ext_addr;
#pragma unroll
        for (int h = 0; h < 2; h++) {
            const uint4 v0 = ld_rlx128(src + s * 512 + h * 256), v1 = ld_rlx128(src + s * 512 + h * 256 + 128);
            sts128(dst + h * 4096, v0.x, v0.y, v0.z, v0.w);
            sts128(dst + h * 4096 + 2048, v1.x, v1.y, v1.z, v1.w);
        }
    }
}
template <int H>
__device__ __forceinline__ void landed_read(uint4 (&v)[4][4], uint32_t main_addr, uint32_t ext_addr, const uint4* src, uint32_t tag) {
    int it = 0;
#pragma unroll 1
    while (true) {
#pragma unroll
        for (int s = 0; s < 4; s++)
#pragma unroll
            for (int k = 0; k < 4; k++) v[s][k] = lds128((4 * H + s < 7 ? main_addr + (4 * H + s) * 8192 : ext_addr) + k * 2048);
        uint32_t bad = 0;
#pragma unroll
        for (int s = 0; s < 4; s++) bad |= tag_bad(v[s], tag);
        if (__builtin_expect(!__any_sync(0xFFFFFFFFu, bad != 0), 1) || ++it > SPIN_LIMIT) break;
        uint32_t mask = 0;
#pragma unroll
        for (int s = 0; s < 4; s++) mask |= __any_sync(0xFFFFFFFFu, tag_bad(v[s], tag) != 0) ? 1u << (4 * H + s) : 0u;
        refetch(main_addr, ext_addr, src, mask);
    }
}
__device__ __forceinline__ float tile_max(const float (&s)[32], int o) {
    float a = s[o], c = s[o + 1];
#pragma unroll
    for (int i = 1; i < 8; i++) { a = fmaxf(a, s[4 * i + o]); c = fmaxf(c, s[4 * i + o + 1]); }
    return fmaxf(a, c);
}
template <int A, int B> __device__ __forceinline__ void init_bars() {
#pragma unroll
    for (int i = A; i < B; i++) mbar_init(BAR(i), i < N_ONE ? 1 : (i < N_EIGHT ? 8 : 4));
}
__device__ __forceinline__ uint32_t perm_off(int p) {
    const int blk = p >> 2, q = p & 3;
    return ((blk >> 2) * 16 + q * 4 + (blk & 3)) * 4;
}

__global__ void __cluster_dims__(2, 1, 1) __launch_bounds__(NTHREADS, 1)
fused_block_kernel(Scratch* __restrict__ scr, const __nv_bfloat16* __restrict__ x, const __nv_bfloat16* __restrict__ cvec,
                   const __nv_bfloat16* __restrict__ wmod, __nv_bfloat16* __restrict__ out, const __nv_bfloat16* __restrict__ wqkv, const __nv_bfloat16* __restrict__ wo,
                   const __nv_bfloat16* __restrict__ wg, const __nv_bfloat16* __restrict__ wu, const __nv_bfloat16* __restrict__ wd,
                   const __grid_constant__ CUtensorMap tm_x, const __grid_constant__ CUtensorMap tm_qkv,
                   const __grid_constant__ CUtensorMap tm_wo, const __grid_constant__ CUtensorMap tm_g,
                   const __grid_constant__ CUtensorMap tm_u, const __grid_constant__ CUtensorMap tm_g3,
                   const __grid_constant__ CUtensorMap tm_u3, const __grid_constant__ CUtensorMap tm_d,
                   const __grid_constant__ CUtensorMap tm_m, const __grid_constant__ CUtensorMap tm_r) {
    extern __shared__ __align__(1024) uint8_t smem_raw[];
    const int bid = blockIdx.x;
    const int j = (bid & 1) + 2 * (bid >> 5);
    const int b = (bid & 31) >> 1;
    const int tid = threadIdx.x;
    const int lane = tid & 31;
    if ((smem_u32(smem_raw) & 0xFFFFFFu) != SB) return;
    TS(0);
    TG(30);
    const int qcol = 56 * j - 8 * (j & 1);
    const int wgi = __shfl_sync(0xFFFFFFFFu, tid >> 7, 0);
    if (wgi == 2) {
        asm volatile("setmaxnreg.dec.sync.aligned.u32 40;");
        const int hw = __shfl_sync(0xFFFFFFFFu, (tid - 256) >> 5, 0);
        if (lane == 0) {
            if (hw == 0) {
                asm volatile("prefetch.tensormap [%0];" ::"l"(&tm_x) : "memory");
                asm volatile("prefetch.tensormap [%0];" ::"l"(&tm_qkv) : "memory");
                init_bars<0, F_HK>();
            }
            if (hw == 1) init_bars<F_HK, F_P>();
            if (hw == 2) init_bars<F_P, R_Q>();
            if (hw == 3) init_bars<R_Q, N_BARS>();
            asm volatile("fence.mbarrier_init.release.cluster;" ::: "memory");
        }
        __syncwarp();
        if (hw == 1 && lane == 0) { mbar_expect_tx(BAR(F_H0), SLOT); mbar_expect_tx(BAR(F_H1), SLOT); }
        __syncwarp();
        asm volatile("barrier.cluster.arrive.relaxed.aligned;" ::: "memory");
        bar_arrive(2, 384);
        if (hw == 0) bar_arrive(3, 128);
        else { bar_arrive(7, 128); bar_sync(3, 128); }
        uint32_t tag = 0;
        if (hw != 0) tag = ld_rlx32(&scr->epoch[bid * 32 + lane]);
        if (hw == 0) {
            TS(1);
            expect_tx_e(BAR(F_X0), 3 * 16384);
            expect_tx_e(BAR(F_X0 + 1), 2 * 16384);
            expect_tx_e(BAR(F_X0 + 2), 2 * 16384);
#pragma unroll 1
            for (int c = 0; c < 7; c++) tma_2d_e(SLOTA(3) + c * 16384, &tm_x, 64 * c, 128 * b, BAR(F_X0) + 8 * ((c >= 3) + (c >= 5)));
#pragma unroll 1
            for (int i = 0; i < 8; i++) {
                if (i == NPRE) bar_sync(7, 128);
                if (i == NPRE) mbar_wait(BAR(R_X), 0);
                if (i == 6) { mbar_wait(BAR(R_V), 0); mbar_wait(BAR(F_HV), 0); }
                const uint32_t bar = BAR(F_K0) + 8 * i;
                expect_tx_e(bar, SLOT);
                tma_2d_e(SB + (i < 6 ? i : i - 4) * SLOT, i < 6 ? &tm_qkv : &tm_wo, qcol + (i < 4 ? DM + DM * (i >> 1) : 0), 224 * (i & 1), bar);
            }
        }
        if (hw == 1 || hw == 2) {
            tag += 1;
            const int w = hw - 1, tile = 2 * b + w;
            if (w == 0) {
                if (lane == 0) {
                    mbar_wait(BAR(F_X0 + 2), 0);
                    l2_prefetch((const uint8_t*)wqkv + bid * 9408, 9408);
                    l2_prefetch((const uint8_t*)wo + bid * 3136, 3136);
#pragma unroll 1
                    for (int m = 0; m < 2; m++) {
                        mbar_wait(BAR(R_KST) + 8 * m, 0);
                        const int idx = (b * 8 + j) * 2 + m;
                        asm volatile("st.release.gpu.global.u32 [%0], %1;" ::"l"(&scr->kvflag[idx * 8]), "r"(tag) : "memory");
                    }
                    mbar_wait(BAR(F_HV), 0);
                    l2_prefetch((const uint8_t*)wg + bid * 12544, 12544);
                    l2_prefetch((const uint8_t*)wu + bid * 12544, 12544);
                    l2_prefetch((const uint8_t*)wd + bid * 12544, 12544);
                }
                __syncwarp();
            } else {
                asm volatile("barrier.cluster.wait.acquire.aligned;" ::: "memory");
                const int nh = b < 2 ? b : 2;
                const int m = (lane >> 1) & 1, h = lane & 1;
                const int idx = ((b - 2 + h) * 8 + j) * 2 + m;
                bool todo = lane < 4 && h >= 2 - nh;
                mbar_wait(BAR(R_K), 0);
                if (nh < 2) {
                    const uint32_t bytes = (2 - nh) * 2 * KVT;
#pragma unroll 1
                    for (uint32_t o = lane * 16; o < bytes; o += 512) {
                        sts128(SLOTA(0) + o, 0, 0, 0, 0);
                        sts128(SLOTA(1) + o, 0, 0, 0, 0);
                    }
                    fence_async_smem();
                    __syncwarp();
                }
                expect_tx_e(BAR(F_HK), nh * 2 * KVT);
                expect_tx_e(BAR(F_HV), nh * 2 * KVT);
                int it = 0;
#pragma unroll 1
                while (__any_sync(0xFFFFFFFFu, todo) && ++it < SPIN_LIMIT) {
                    if (todo && ld_acq32(&scr->kvflag[idx * 8]) == tag) {
                        asm volatile("fence.proxy.async.global;" ::: "memory");
                        bulk_g2s(SLOTA(0) + m * SLOT + h * 2 * KVT, scr->kv + (size_t)idx * 2 * KVT, 2 * KVT, BAR(F_HK) + 8 * m);
                        todo = false;
                    }
                }
            }
            const int s = lane >> 2, ww = lane & 3;
#pragma unroll 1
            for (int ph = 0; ph < 3; ph++) {
                const uint4* src;
                uint32_t dst = s < 7 ? (w ? SLOTA(0) : SLOTA(4)) + s * 8192 : SB + OFF_QX + (w ? 0 : 16384);
                uint32_t bar, todo = 0x11111111u;
                if (ph == 0) {
                    mbar_wait(BAR(w ? R_ATT : R_Q), 0);
                    if (w) {
                        expect_tx_e(BAR(F_R1), 8192);
                        tma_2d_e(SB + OFF_QX + 8192, &tm_r, qcol, 64 * tile, BAR(F_R1));
                    }
                    mbar_wait(BAR(w ? R_XR : R_WM), 0);
                    src = scr->o + (size_t)tile * 4096;
                    bar = BAR(F_O0) + 8 * w;
                    expect_tx_e(bar, 65536);
                } else if (ph == 1) {
                    if (!w) {
                        expect_tx_e(BAR(F_R0), 8192);
                        tma_2d_e(SB + OFF_QX, &tm_r, qcol, 64 * tile, BAR(F_R0));
                    }
                    mbar_wait(BAR(R_O0) + 8 * w, 0);
                    mbar_wait(BAR(R_ATT), 0);
                    src = scr->x2 + (size_t)tile * 4096;
                    bar = BAR(F_Y0) + 8 * w;
                    expect_tx_e(bar, 65536);
                } else {
                    if (w) {
                        mbar_wait(BAR(R_Y1), 0);
                        if (lane == 0)
                            asm volatile("mbarrier.arrive.release.cluster.shared::cluster.b64 _, [%0];" ::"r"(BAR(R_PR) + (cta_win() ^ (1u << 24))) : "memory");
                    }
                    bar = BAR(F_P) + 8 * (4 * w + (s & 3));
                    if (lane < 16 && ww == 0) mbar_expect_tx(bar, 8192);
                    mbar_wait(BAR(R_H0) + 8 * w, 0);
                    src = s == 3 ? scr->x2 + ((size_t)tile * 8 + j - 3) * 512 : scr->part + ((size_t)tile * 8 + j) * 2048 - (s > 3 ? s * 512 : 0);
                    dst = s == 3 ? SB + OFF_QX + (w ? 0 : 12288) : SLOTA(0) + w * SLOT + s * 8192;
                    todo = 0x1111u;
                }
                src += s * 512;
                const uint2* hp = scr->hint + (ph < 2 ? ph * 32 + tile : 64 + tile * 8 + j) * 8 * HS + s * HS + ww;
                uint32_t pend = 0;
                int it = 0;
#pragma unroll 1
                while (todo && ++it < SPIN_LIMIT) {
                    const uint2 hv = ld_rlx64(hp);
                    uint32_t ok = __ballot_sync(0xFFFFFFFFu, hv.x == tag && hv.y == tag);
                    if (ph == 2) ok |= 0xF000u;
                    ok &= ok >> 1;
                    ok &= ok >> 2;
                    ok &= todo;
                    if (ph == 1 && ok == todo && lane == 0) mbar_arrive(BAR(F_S0) + 8 * w);
                    if ((pend >> lane) & 1u) bulk_g2s(dst, src, 8192, bar);
                    pend = ok;
                    todo &= ~ok;
                }
                if ((pend >> lane) & 1u) bulk_g2s(dst, src, 8192, bar);
                __syncwarp();
            }
            return;
        }
        if (hw == 3) {
            tag += 1;
            if (bid < 112) {
                const int col = 896 + bid * 16 + (lane & 1) * 8;
                const uint32_t slab = SB + OFF_QX + 16384, sil = slab + 7168;
#pragma unroll 1
                for (int i = 0; i < 7; i++) {
                    const uint32_t cc = ((const uint32_t*)cvec)[lane + 32 * i];
                    sts32(sil + (lane + 32 * i) * 4, pack2(silu_bf(bf_lo(cc)), silu_bf(bf_hi(cc))));
                }
                float a[8];
#pragma unroll
                for (int i = 0; i < 8; i++) a[i] = 0.f;
                mbar_wait(BAR(R_X), 0);
#pragma unroll 1
                for (int h = 0; h < 2; h++) {
                    __syncwarp();
                    expect_tx_e(BAR(F_WM), 7168);
                    tma_2d_e(slab, &tm_m, 896 + bid * 16, 224 * h, BAR(F_WM));
                    mbar_wait(BAR(F_WM), h);
#pragma unroll 2
                    for (int i = 0; i < 14; i++) {
                        const uint32_t sv = lds32(sil + (112 * h + 8 * i + (lane >> 2)) * 4);
                        fma8(a, (lane & 2) ? bf_hi(sv) : bf_lo(sv), lds128(slab + i * 512 + lane * 16));
                    }
                }
                {
                    bool up = lane & 16;
#pragma unroll
                    for (int i = 0; i < 4; i++) {
                        float keep = up ? a[i + 4] : a[i], send = up ? a[i] : a[i + 4];
                        a[i] = keep + __shfl_xor_sync(0xFFFFFFFFu, send, 16);
                    }
                    up = lane & 8;
#pragma unroll
                    for (int i = 0; i < 2; i++) {
                        float keep = up ? a[i + 2] : a[i], send = up ? a[i] : a[i + 2];
                        a[i] = keep + __shfl_xor_sync(0xFFFFFFFFu, send, 8);
                    }
#pragma unroll
                    for (int o = 2; o < 8; o <<= 1) {
                        a[0] += __shfl_xor_sync(0xFFFFFFFFu, a[0], o);
                        a[1] += __shfl_xor_sync(0xFFFFFFFFu, a[1], o);
                    }
                }
                if ((lane & 6) == 0) st_rlx64(&scr->mod[(col >> 1) + (lane >> 3)], pack2(a[0], a[1]), tag);
            }
            __syncwarp();
            if (lane == 0) mbar_arrive(BAR(R_WM));
            mbar_wait(BAR(F_HV), 0);
#pragma unroll 1
            for (int h = 0; h < 2; h++) {
                uint2 mv[8];
                int it = 0;
                uint32_t bad;
#pragma unroll 1
                do {
                    bad = 0;
#pragma unroll
                    for (int i = 0; i < 7; i++) mv[i] = ld_rlx64(&scr->mod[672 + 224 * h + lane + 32 * i]);
                    mv[7] = ld_rlx64(&scr->mod[448 + 672 * h + 28 * j + (lane < 28 ? lane : 0)]);
#pragma unroll
                    for (int i = 0; i < 8; i++) bad |= mv[i].y ^ tag;
                } while (bad && ++it < SPIN_LIMIT);
#pragma unroll
                for (int i = 0; i < 7; i++)
                    sts32(SB + (h ? OFF_C2 : OFF_S2) + perm_off(lane + 32 * i), h ? hfma2(mv[i].x, 0x3F803F80u, 0x3F803F80u) : mv[i].x);
                if (lane < 28) sts32(SB + (h ? OFF_GB : OFF_GA) + lane * 4, mv[7].x);
            }
            __syncwarp();
            if (lane == 0) mbar_arrive(BAR(F_MOD2));
            mbar_wait(BAR(F_O0), 0);
            scr->epoch[bid * 32 + lane] = tag;
        }
#pragma unroll 1
        for (int g = 0; g < N_ITEMS; g++) {
            const int use = g / NRING, pos = g - use * NRING;
            if ((pos & 1) != (hw & 1)) continue;
            const uint32_t full = BAR(F_RING) + 8 * pos;
            const uint32_t dst = SB + ring_slot(pos) * SLOT;
            if (use == 0) mbar_wait(BAR(g == 0 ? R_ATT : (g < 3 ? R_WO : R_Y0)), 0);
            else mbar_wait(BAR(E_RING) + 8 * pos, (use - 1) & 1);

            expect_tx_e(full, SLOT);
            if (g >= 14) {
                const int m = g - 14;
                const int k = (0x33221010 >> (4 * m)) & 3, par = (0xAC >> m) & 1;
                const int sl = (j + 2 * k + 2) & 7;
                tma_2d_e(dst, &tm_d, 56 * sl - 8 * (sl & 1), 224 * (j ^ par), full);
            } else {
                const bool small = g < 2;
                const int m = g - 2;
                const int col = 224 * j + (small ? ((j & 1) ? 0 : 192) : 32 * (j & 1) + 64 * (m >> 2));
                const int row = small ? 224 * (g & 1) : 112 * (m & 3);
                tma_2d_e(dst, small ? &tm_g3 : &tm_g, col, row, full);
                tma_2d_e(dst + SLOT / 2, small ? &tm_u3 : &tm_u, col, row, full);
            }
        }
    } else {
        const int w = wgi, t = tid & 127, warp = t >> 5, r = lane >> 2, q = lane & 3;
        const int tile = 2 * b + w;
        const uint32_t jo = j & 1;

        const int mt = bid < 112 ? bid : 111;
        const int mcg = mt % 28, mrs = mt / 28;
        const int mrow = 112 * mrs + (tid >> 2), mrow1 = tid < 192 ? mrow + 64 : mrow;
        const uint4 wm0 = ldg128(wmod + (size_t)mrow * 2688 + mcg * 32 + (tid & 3) * 8);
        const uint4 wm1 = ldg128(wmod + (size_t)mrow1 * 2688 + mcg * 32 + (tid & 3) * 8);
        unsigned short cv0, cv1;
        asm volatile("ld.global.nc.u16 %0, [%1];" : "=h"(cv0) : "l"(cvec + mrow));
        asm volatile("ld.global.nc.u16 %0, [%1];" : "=h"(cv1) : "l"(cvec + mrow1));
        uint32_t tag = ld_rlx32(&scr->epoch[bid * 32 + lane]);
        asm volatile("barrier.cluster.arrive.relaxed.aligned;" ::: "memory");
        TS(12);
        tag += 1;
        if (bid < 112) {
            float a[8];
#pragma unroll
            for (int i = 0; i < 8; i++) a[i] = 0.f;
            fma8(a, silu_bf(bf_lo(cv0)), wm0);
            fma8(a, tid < 192 ? silu_bf(bf_lo(cv1)) : 0.f, wm1);
            const float v = reduce8(a, lane);
            sts32(SB + OFF_RED + ((tid >> 5) * 32 + 8 * (lane & 3) + (lane >> 2)) * 4, __float_as_uint(v));
            if (tid < 32) {
                bar_sync(1, 256);
                if (lane < 8 * NCOPY) {
                    float4 acc = make_float4(0.f, 0.f, 0.f, 0.f);
#pragma unroll
                    for (int k = 0; k < 8; k++) {
                        const uint4 u = lds128(SB + OFF_RED + k * 128 + (lane & 7) * 16);
                        acc.x += __uint_as_float(u.x); acc.y += __uint_as_float(u.y);
                        acc.z += __uint_as_float(u.z); acc.w += __uint_as_float(u.w);
                    }
                    st_rlx128(&scr->modp[(lane >> 3) * 896 + mrs * 224 + mcg * 8 + (lane & 7)], (__float_as_uint(acc.x) & ~15u) | (tag & 15u),
                              (__float_as_uint(acc.y) & ~15u) | ((tag >> 4) & 15u), (__float_as_uint(acc.z) & ~15u) | ((tag >> 8) & 15u),
                              (__float_as_uint(acc.w) & ~15u) | ((tag >> 12) & 15u));
                }
                __syncwarp();
            } else {
                bar_arrive(1, 256);
            }
        }
        TS(13);
        asm volatile("setmaxnreg.inc.sync.aligned.u32 232;");
        bar_sync(2, 384);
        uint32_t rn1[4];
        uint4 mp[4];
        const int mi = (tid < 224 ? tid : 0) + ((bid >> 1) % NCOPY) * 896;
        uint32_t af[28][4];
        {
            const int xr_ = 64 * w + 16 * warp + (lane & 7) + 8 * ((lane >> 3) & 1);
            const uint32_t xa = SLOTA(3) + xr_ * 128;
            const uint32_t hi = lane >> 4, sw = lane & 7;
            float c1[2][4], c2[2][4], c3[2][4];
#pragma unroll
            for (int i = 0; i < 4; i++) c1[0][i] = c1[1][i] = c2[0][i] = c2[1][i] = c3[0][i] = c3[1][i] = 0.f;
            auto x_group = [&](auto GC) {
                constexpr int g = decltype(GC)::value;
                constexpr int s0 = g == 0 ? 0 : 4 + 8 * g, s1 = 12 + 8 * g;
                mbar_wait(BAR(F_X0 + g), 0);
#pragma unroll
                for (int s = s0; s < s1; s++) ldsm4(af[s], xa + (s >> 2) * 16384 + (((2 * (s & 3) + hi) ^ sw) << 4));
#pragma unroll
                for (int s = s0; s < s1; s++) {
                    hmma8(c1[0], af[s][0], af[s][1], af[s][0]);
                    hmma8(c2[0], af[s][0], af[s][1], af[s][1]);
                    hmma8(c1[1], af[s][2], af[s][3], af[s][2]);
                    hmma8(c2[1], af[s][2], af[s][3], af[s][3]);
                    hmma(c3[s & 1], af[s], 0x3F803F80u, 0x3F803F80u);
                }
            };
            x_group(IC<0>{}); x_group(IC<1>{}); x_group(IC<2>{});
            {
#pragma unroll
                for (int k = 0; k < 4; k++) mp[k] = ld_rlx128(&scr->modp[k * 224 + mi]);
                __syncwarp();
                if (lane == 0) mbar_arrive(BAR(R_X));
            }
            TS(14);
            const int src = (lane & ~3) | (r >> 1);
            const float qa = __shfl_sync(0xFFFFFFFFu, (r & 1) ? c1[0][1] + c1[1][1] : c1[0][0] + c1[1][0], src);
            const float qb = __shfl_sync(0xFFFFFFFFu, (r & 1) ? c2[0][3] + c2[1][3] : c2[0][2] + c2[1][2], src);
            const float ma = (c3[0][0] + c3[1][0]) * (1.0f / DM), mb = (c3[0][2] + c3[1][2]) * (1.0f / DM);
            const float rsa = bf_lo(pack2(rsqrtf(fmaxf(fmaf(-ma, ma, qa * (1.0f / DM)), 0.f) + 1e-5f), 0.f));
            const float rsb = bf_lo(pack2(rsqrtf(fmaxf(fmaf(-mb, mb, qb * (1.0f / DM)), 0.f) + 1e-5f), 0.f));
            rn1[0] = pack2(rsa, rsa); rn1[1] = pack2(-ma * rsa, -ma * rsa);
            rn1[2] = pack2(rsb, rsb); rn1[3] = pack2(-mb * rsb, -mb * rsb);
        }
        {
#pragma unroll
            for (int s = 0; s < 28; s++) {
                af[s][0] = hfma2(af[s][0], rn1[0], rn1[1]);
                af[s][1] = hfma2(af[s][1], rn1[2], rn1[3]);
                af[s][2] = hfma2(af[s][2], rn1[0], rn1[1]);
                af[s][3] = hfma2(af[s][3], rn1[2], rn1[3]);
                pin(af[s]);
            }
            int it = 0;
            uint32_t bad;
#pragma unroll 1
            while (true) {
                bad = 0;
#pragma unroll
                for (int k = 0; k < 4; k++)
                    bad |= (((mp[k].x & 15u) | ((mp[k].y & 15u) << 4) | ((mp[k].z & 15u) << 8) | ((mp[k].w & 15u) << 12)) ^ tag) & 0xFFFFu;
                if (!bad || ++it > SPIN_LIMIT) break;
#pragma unroll
                for (int k = 0; k < 4; k++) mp[k] = ld_rlx128(&scr->modp[k * 224 + mi]);
            }
            TS(29);
            if (tid < 224) {
                float f[4] = {0.f, 0.f, 0.f, 0.f};
#pragma unroll
                for (int k = 0; k < 4; k++) {
                    f[0] += __uint_as_float(mp[k].x & ~15u); f[1] += __uint_as_float(mp[k].y & ~15u);
                    f[2] += __uint_as_float(mp[k].z & ~15u); f[3] += __uint_as_float(mp[k].w & ~15u);
                }
                uint32_t p0 = pack2(f[0], f[1]), p1 = pack2(f[2], f[3]);
                const bool isc = tid >= 112;
                if (isc) { p0 = hfma2(p0, 0x3F803F80u, 0x3F803F80u); p1 = hfma2(p1, 0x3F803F80u, 0x3F803F80u); }
                const int pp = 2 * (isc ? tid - 112 : tid);
                const uint32_t tb = SB + (isc ? OFF_C1 : OFF_S1);
                sts32(tb + perm_off(pp), p0);
                sts32(tb + perm_off(pp + 1), p1);
            }
        }
        bar_sync(1, 256);
        TS(2);

        float accK[28], accV[28], accQ[28];
        auto k_group = [&](auto GC) {
            constexpr int g = decltype(GC)::value;
            constexpr int s0 = g == 0 ? 0 : 8 * g - 2, s1 = g == 3 ? 28 : 8 * g + 6;
#pragma unroll
            for (int s = s0; s < s1; s += 2) {
                const uint4 c4 = lds128(SB + OFF_C1 + (s >> 1) * 64 + q * 16), s4 = lds128(SB + OFF_S1 + (s >> 1) * 64 + q * 16);
                af[s][0] = hfma2(af[s][0], c4.x, s4.x);
                af[s][1] = hfma2(af[s][1], c4.x, s4.x);
                af[s][2] = hfma2(af[s][2], c4.y, s4.y);
                af[s][3] = hfma2(af[s][3], c4.y, s4.y);
                af[s + 1][0] = hfma2(af[s + 1][0], c4.z, s4.z);
                af[s + 1][1] = hfma2(af[s + 1][1], c4.z, s4.z);
                af[s + 1][2] = hfma2(af[s + 1][2], c4.w, s4.w);
                af[s + 1][3] = hfma2(af[s + 1][3], c4.w, s4.w);
                pin(af[s]);
                pin(af[s + 1]);
            }
            if ((g & 1) == 0) mbar_wait(BAR(F_K0 + (g >> 1)), 0);
            WG_FENCE();
#pragma unroll
            for (int s = s0; s < s1; s++)
                wgmma_n56_t1(accK, af[s], mk_desc16(jo, SLOTA(s / 14) + (s % 14) * 2048, 0, 1024, 1), s != 0);
            if (g < 3) mbar_wait(BAR(F_X0), 0);
        };
        k_group(IC<0>{}); k_group(IC<1>{}); k_group(IC<2>{}); k_group(IC<3>{});
        WG_COMMIT();
        TS(28);
        mbar_wait(BAR(F_V0), 0);
        WG_FENCE();
#pragma unroll
        for (int s = 0; s < 7; s++) wgmma_n56_t1(accV, af[s], mk_desc16(jo, SLOTA(2) + s * 2048, 0, 1024, 1), s != 0);
        WG_COMMIT();
        mbar_wait(BAR(R_X), 0);
        WG_WAIT(1);
        pin(accK);
        if (lane == 0) mbar_arrive(BAR(R_K));
        store_kv(SLOTA(6) + w * KVT, scr->kv + (size_t)((b * 8 + j) * 4 + w) * KVT, accK, warp, lane, BAR(R_KST));
        fence_async_smem();
        WG_FENCE();
#pragma unroll
        for (int s = 7; s < 14; s++) wgmma_n56_t1(accV, af[s], mk_desc16(jo, SLOTA(2) + s * 2048, 0, 1024, 1), 1);
        mbar_wait(BAR(F_V1), 0);
        WG_FENCE();
#pragma unroll
        for (int s = 0; s < 14; s++) wgmma_n56_t1(accV, af[14 + s], mk_desc16(jo, SLOTA(3) + s * 2048, 0, 1024, 1), 1);
        WG_COMMIT();
        mbar_wait(BAR(F_Q0), 0);
        WG_FENCE();
#pragma unroll
        for (int s = 0; s < 7; s++) wgmma_n56_t1(accQ, af[s], mk_desc16(jo, SLOTA(4) + s * 2048, 0, 1024, 1), s != 0);
        WG_COMMIT();
        WG_WAIT(1);
        pin(accV);
        if (lane == 0) mbar_arrive(BAR(R_V));
        store_kv(SLOTA(6) + 2 * KVT + w * KVT, scr->kv + (size_t)((b * 8 + j) * 4 + 2 + w) * KVT, accV, warp, lane, BAR(R_VST));
        fence_async_smem();
        WG_FENCE();
#pragma unroll
        for (int s = 7; s < 14; s++) wgmma_n56_t1(accQ, af[s], mk_desc16(jo, SLOTA(4) + s * 2048, 0, 1024, 1), 1);
        mbar_wait(BAR(F_Q1), 0);
        WG_FENCE();
#pragma unroll
        for (int s = 0; s < 14; s++) wgmma_n56_t1(accQ, af[14 + s], mk_desc16(jo, SLOTA(5) + s * 2048, 0, 1024, 1), 1);
        WG_COMMIT();
        WG_WAIT(0);
        pin(accQ);
        if (lane == 0) mbar_arrive(BAR(R_Q));
        {
            uint32_t p[14];
#pragma unroll
            for (int i = 0; i < 14; i++) p[i] = pack2(accQ[2 * i], accQ[2 * i + 1]);
            const uint32_t qa = SB + OFF_QX + w * 8192 + t * 16;
            const bool lo = q < 2;
            sts128(qa, p[0], p[1], p[2], p[3]);
            sts128(qa + 2048, p[4], p[5], lo ? p[6] : 0u, lo ? p[7] : 0u);
            sts128(qa + 4096, lo ? 0u : p[6], lo ? 0u : p[7], p[8], p[9]);
            sts128(qa + 6144, p[10], p[11], p[12], p[13]);
        }
        bar_sync(1, 256);
        TS(3);

        const float SC = 0.18898223650461362f * 1.4426950408889634f;
        const int d0 = 16 * warp + r - 2 * q;
        uint32_t nmask[9];
#pragma unroll
        for (int k = 0; k < 9; k++) {
            asm("shl.b32 %0, %1, %2;" : "=r"(nmask[k]) : "r"(0xFFFFFFFFu), "r"(max(16 * (d0 - 8 * k + 9), 0)));
            asm volatile("" : "+r"(nmask[k]));
        }
#pragma unroll 1
        for (int u = 0; u < 2; u++) {
            uint32_t qf[2][4];
            {
                const uint32_t qa = SB + OFF_QX + u * 8192 + w * 4096 + t * 16;
                const uint4 q0 = lds128(qa), q1 = lds128(qa + 2048);
                qf[0][0] = q0.x; qf[0][1] = q0.y; qf[0][2] = q0.z; qf[0][3] = q0.w;
                qf[1][0] = q1.x; qf[1][1] = q1.y; qf[1][2] = q1.z; qf[1][3] = q1.w;
            }
            const int first = 2 * b + u - 4;
            const uint32_t kh = (SLOTA(0) + u * KVT + w * 3072) >> 4;
            const uint32_t k3 = ((u ? SLOTA(6) : SLOTA(0) + 3 * KVT) + w * 3072) >> 4;
            const uint32_t v3 = ((u ? SLOTA(6) + 2 * KVT : SLOTA(1) + 3 * KVT) + w * 3072) >> 4;
            const uint32_t k4 = (SLOTA(6) + u * KVT + w * 3072) >> 4;
            float s[5][32];
            {
                const float init = first >= 0 ? 0.f : -INFINITY;
#pragma unroll
                for (int i = 0; i < 32; i++) s[0][i] = init;
            }
            pin(s[0]);
            pin(qf[0]);
            pin(qf[1]);
            WG_FENCE();
            wgmma_n64_t0(s[4], qf[0], mk_desc16(k4, 0, 1024, 128, 0), 0);
            wgmma_n64_t0(s[4], qf[1], mk_desc16(k4, 2048, 1024, 128, 0), 1);
            mbar_wait(BAR(F_HK), 0);
            WG_FENCE();
            wgmma_n64_t0(s[0], qf[0], mk_desc16(kh, 0, 1024, 128, 0), 1);
            wgmma_n64_t0(s[0], qf[1], mk_desc16(kh, 2048, 1024, 128, 0), 1);
            WG_COMMIT();
            wgmma_n64_t0(s[3], qf[0], mk_desc16(k3, 0, 1024, 128, 0), 0);
            wgmma_n64_t0(s[3], qf[1], mk_desc16(k3, 2048, 1024, 128, 0), 1);
#pragma unroll
            for (int kt = 2; kt >= 1; kt--) {
                wgmma_n64_t0(s[kt], qf[0], mk_desc16(kh, kt * KVT, 1024, 128, 0), 0);
                wgmma_n64_t0(s[kt], qf[1], mk_desc16(kh, kt * KVT + 2048, 1024, 128, 0), 1);
            }
            WG_COMMIT();
            WG_WAIT(1);
            pin(s[0]);
            pin(s[4]);
#pragma unroll
            for (int i = 0; i < 8; i++)
#pragma unroll
                for (int rh = 0; rh < 2; rh++)
#pragma unroll
                    for (int e = 0; e < 2; e++)
                        s[4][4 * i + 2 * rh + e] = (8 * i + e - 8 * rh <= d0) ? s[4][4 * i + 2 * rh + e] : s[0][4 * i + 2 * rh + e];
            float m0 = tile_max(s[4], 0), m1 = tile_max(s[4], 2);
            pin(s[4]);
            WG_WAIT(0);
#pragma unroll
            for (int kt = 1; kt < 4; kt++) pin(s[kt]);
#pragma unroll
            for (int kt = 1; kt < 4; kt++) {
                const float t0 = tile_max(s[kt], 0), t1 = tile_max(s[kt], 2);
                if (first + kt >= 0) { m0 = fmaxf(m0, t0); m1 = fmaxf(m1, t1); }
            }
            m0 = quad_max(m0);
            m1 = quad_max(m1);
            m0 *= -SC;
            m1 *= -SC;
            float o[16], ls[2][2] = {{0.f, 0.f}, {0.f, 0.f}};
            uint32_t pf[5][4][4];
#pragma unroll
            for (int kk = 0; kk < 4; kk++) {
                const int kt = kk == 0 ? 4 : 4 - kk;
                const bool ok = kt == 4 || first + kt >= 0;
                const float n0 = ok ? m0 : -INFINITY, n1 = ok ? m1 : -INFINITY;
#pragma unroll
                for (int i = 0; i < 8; i++) {
                    const float p0 = ex2f(fmaf(s[kt][4 * i], SC, n0)), p1 = ex2f(fmaf(s[kt][4 * i + 1], SC, n0));
                    const float p2 = ex2f(fmaf(s[kt][4 * i + 2], SC, n1)), p3 = ex2f(fmaf(s[kt][4 * i + 3], SC, n1));
                    ls[0][0] += p0; ls[0][1] += p1; ls[1][0] += p2; ls[1][1] += p3;
                    pf[kt][i >> 1][2 * (i & 1)] = pack2(p0, p1);
                    pf[kt][i >> 1][2 * (i & 1) + 1] = pack2(p2, p3);
                }
                if (kt == 4) {
#pragma unroll
                    for (int i = 0; i < 8; i++)
#pragma unroll
                        for (int rh = 0; rh < 2; rh++) {
                            const uint32_t pv = pf[4][i >> 1][2 * (i & 1) + rh];
                            pf[0][i >> 1][2 * (i & 1) + rh] = pv & nmask[i - rh + 1];
                            pf[4][i >> 1][2 * (i & 1) + rh] = pv & ~nmask[i - rh + 1];
                        }
                }
                if (kk == PV_SPLIT || kk == 3) {
#pragma unroll
                    for (int k2 = (kk == 3 && PV_SPLIT >= 0 && PV_SPLIT < 3 ? PV_SPLIT + 1 : 0); k2 <= kk; k2++) {
                        const int t2 = k2 == 0 ? 4 : 4 - k2;
#pragma unroll
                        for (int ks = 0; ks < 4; ks++) pin(pf[t2][ks]);
                        if (t2 == 4) {
#pragma unroll
                            for (int ks = 0; ks < 4; ks++) pin(pf[0][ks]);
                            mbar_wait(BAR(F_HV), 0);
                        }
                    }
                    WG_FENCE();
#pragma unroll
                    for (int k2 = (kk == 3 && PV_SPLIT >= 0 && PV_SPLIT < 3 ? PV_SPLIT + 1 : 0); k2 <= kk; k2++) {
                        const int t2 = k2 == 0 ? 4 : 4 - k2;
#pragma unroll
                        for (int ks = 0; ks < 4; ks++) {
                            const uint64_t dv = t2 == 4 ? mk_desc16(k4, 2 * KVT + ks * 256, 128, 1024, 0)
                                              : t2 == 3 ? mk_desc16(v3, ks * 256, 128, 1024, 0)
                                                        : mk_desc16(kh, SLOT + t2 * KVT + ks * 256, 128, 1024, 0);
                            wgmma_n32_t1(o, pf[t2][ks], dv, (k2 | ks) != 0);
                        }
                        if (t2 == 4) {
#pragma unroll
                            for (int ks = 0; ks < 4; ks++) wgmma_n32_t1(o, pf[0][ks], mk_desc16(kh, SLOT + ks * 256, 128, 1024, 0), 1);
                        }
                    }
                    WG_COMMIT();
                }
            }
            const float il0 = __fdividef(1.0f, quad_sum(ls[0][0] + ls[0][1])), il1 = __fdividef(1.0f, quad_sum(ls[1][0] + ls[1][1]));
            WG_WAIT(0);
            pin(o);
            uint32_t pk[8];
#pragma unroll
            for (int i = 0; i < 4; i++) {
                pk[2 * i] = pack2(o[4 * i] * il0, o[4 * i + 1] * il0);
                pk[2 * i + 1] = pack2(o[4 * i + 2] * il1, o[4 * i + 3] * il1);
            }
            {
                uint32_t f[6];
#pragma unroll
                for (int i = 0; i < 4; i++) f[i] = w ? pk[i + 4] : pk[i];
                f[4] = w ? pk[2] : pk[4];
                f[5] = w ? pk[3] : pk[5];
                const uint32_t part0 = w ? pk[0] : pk[6], part1 = w ? pk[1] : pk[7];
                const uint32_t got = __shfl_xor_sync(0xFFFFFFFFu, w ? part0 : part1, 2);
                const bool lo = q < 2;
                const uint32_t ex = (lo == (w == 0)) ? (lo ? part0 : part1) : got;
                uint4* dst = scr->o + (((2 * b + u) * 8 + j) * 4 + 2 * w) * 128 + t;
                st_rlx128(dst, f[0], f[1], f[2], prmt(f[3], tag, 0x1054));
                st_rlx128(dst + 128, f[4], f[5], ex, prmt(f[3], tag, 0x3254));
                if (lane == 0) st_rlx32((uint32_t*)(scr->hint + (2 * b + u) * 8 * HS + j * HS + warp) + w, tag);
            }
            TS(4 + u);
        }
        if (lane == 0) mbar_arrive(BAR(R_ATT));

        const uint32_t land = (w ? SLOTA(0) : SLOTA(4)) + t * 16, land_x = SB + OFF_QX + (w ? 0 : 16384) + t * 16;
        uint32_t xr[14];
        {
            mbar_wait(BAR(F_R0) + 8 * w, 0);
            const uint32_t ra = SB + OFF_QX + w * 8192 + (16 * warp + (lane & 15)) * 128;
#pragma unroll
            for (int i = 0; i < 3; i++) {
                uint32_t f[4];
                ldsm4(f, ra + (((jo + 2 * i + (lane >> 4)) ^ (lane & 7)) << 4));
                xr[4 * i] = f[0]; xr[4 * i + 1] = f[1]; xr[4 * i + 2] = f[2]; xr[4 * i + 3] = f[3];
            }
            ldsm2(xr[12], xr[13], ra + (((jo + 6) ^ (lane & 7)) << 4));
            __syncwarp();
            if (w == 0 && lane == 0) mbar_arrive(BAR(R_XR));
        }
        float accO[28];
        mbar_wait(BAR(F_O0) + 8 * w, 0);
        TS(6);
        auto wo_half = [&](auto HC) {
            constexpr int hf = decltype(HC)::value;
            uint4 v[4][4];
            landed_read<hf>(v, land, land_x, scr->o + (size_t)tile * 4096 + t, tag);
            if (hf == 1 && lane == 0) mbar_arrive(BAR(R_O0) + 8 * w);
            const bool lo = q < 2;
#pragma unroll
            for (int s = 0; s < 4; s++) {
                const int k0 = 14 * hf + 7 * (s >> 1) + 3 * (s & 1), k6 = 14 * hf + 7 * (s >> 1) + 6;
                const uint32_t e0 = v[s][1].z, e1 = v[s][3].z;
                const uint32_t got = __shfl_xor_sync(0xFFFFFFFFu, lo ? e1 : e0, 2);
                af[k0][0] = v[s][0].x; af[k0][1] = v[s][0].y; af[k0][2] = v[s][0].z;
                af[k0][3] = prmt(v[s][0].w, v[s][1].w, 0x7632);
                af[k0 + 1][0] = v[s][1].x; af[k0 + 1][1] = v[s][1].y;
                af[k0 + 1][2] = lo ? e0 : got; af[k0 + 1][3] = lo ? got : e1;
                af[k0 + 2][0] = v[s][2].x; af[k0 + 2][1] = v[s][2].y; af[k0 + 2][2] = v[s][2].z;
                af[k0 + 2][3] = prmt(v[s][2].w, v[s][3].w, 0x7632);
                af[k6][2 * (s & 1)] = v[s][3].x; af[k6][2 * (s & 1) + 1] = v[s][3].y;
            }
#pragma unroll
            for (int s = 0; s < 14; s++) pin(af[14 * hf + s]);
            mbar_wait(BAR(F_WO0 + hf), 0);
            WG_FENCE();
#pragma unroll
            for (int s = 0; s < 14; s++)
                wgmma_n56_t1(accO, af[14 * hf + s],
                             mk_desc16(jo, SLOTA(2 + hf) + ((s / 7) * 14 + kstep_group<4>(s % 7)) * 1024, 0, 1024 * kstep_gap(s % 7), 1),
                             (hf | s) != 0);
        };
        wo_half(IC<0>{});
        wo_half(IC<1>{});
        WG_COMMIT();
        mbar_wait(BAR(F_MOD2), 0);
        WG_WAIT(0);
        pin(accO);
        if (lane == 0) mbar_arrive(BAR(R_WO));
        {
            float s0 = 0.f, s1 = 0.f;
#pragma unroll
            for (int i = 0; i < 7; i++) {
                const uint32_t g = lds32(SB + OFF_GA + (4 * i + q) * 4);
                accO[4 * i] = fmaf(bf_lo(g), accO[4 * i], bf_lo(xr[2 * i]));
                accO[4 * i + 1] = fmaf(bf_hi(g), accO[4 * i + 1], bf_hi(xr[2 * i]));
                accO[4 * i + 2] = fmaf(bf_lo(g), accO[4 * i + 2], bf_lo(xr[2 * i + 1]));
                accO[4 * i + 3] = fmaf(bf_hi(g), accO[4 * i + 3], bf_hi(xr[2 * i + 1]));
                s0 += accO[4 * i] + accO[4 * i + 1];
                s1 += accO[4 * i + 2] + accO[4 * i + 3];
            }
            uint32_t p[14];
#pragma unroll
            for (int i = 0; i < 14; i++) p[i] = pack2(accO[2 * i], accO[2 * i + 1]);
            publish14(scr->x2 + ((size_t)tile * 8 + j) * 512 + t, p, tag);
            s0 *= 1.0f / 14;
            s1 *= 1.0f / 14;
            float m0 = 0.f, m1 = 0.f;
#pragma unroll
            for (int i = 0; i < 7; i++) {
                float d;
                d = accO[4 * i] - s0; m0 = fmaf(d, d, m0);
                d = accO[4 * i + 1] - s0; m0 = fmaf(d, d, m0);
                d = accO[4 * i + 2] - s1; m1 = fmaf(d, d, m1);
                d = accO[4 * i + 3] - s1; m1 = fmaf(d, d, m1);
            }
            m0 = quad_sum(fmaf(14.f * s0, s0, m0));
            m1 = quad_sum(fmaf(14.f * s1, s1, m1));
            s0 = quad_sum(s0) * 0.25f;
            s1 = quad_sum(s1) * 0.25f;
            m0 = fmaxf(fmaf(-56.f * s0, s0, m0), 0.f);
            m1 = fmaxf(fmaf(-56.f * s1, s1, m1), 0.f);
            if (q < 2)
                st_rlx64(scr->st2 + ((size_t)tile * 8 + j) * 64 + 16 * warp + r + 8 * q, prmt(__float_as_uint(q ? s1 : s0), __float_as_uint(q ? m1 : m0), 0x3215),
                         prmt(__float_as_uint(q ? m1 : m0), tag, 0x3254));
            if (lane == 0) st_rlx64(scr->hint + (32 + tile) * 8 * HS + j * HS + warp, tag, tag);
        }
        TS(7);

        uint32_t hh[14][4];
        auto ring_get = [&](auto IC_) -> uint32_t {
            constexpr int g = decltype(IC_)::value;
            mbar_wait(BAR(F_RING + g % NRING), (g / NRING) & 1);
            return SLOTA(ring_slot(g % NRING)) >> 4;
        };
        auto ring_put = [&](auto IC_) {
            if (lane == 0) mbar_arrive(BAR(E_RING + decltype(IC_)::value % NRING));
        };
        const uint32_t hs = SB + OFF_QX + (w ? 0 : 12288) + t * 16;
        {
            uint32_t rn[2][2];
            mbar_wait(BAR(F_S0) + 8 * w, 0);
            {
                uint2 st[4];
                const uint2* sp = scr->st2 + ((size_t)tile * 8 + 2 * q) * 64 + 16 * warp + r;
                int it = 0;
#pragma unroll 1
                do {
                    st[0] = ld_rlx64(sp); st[1] = ld_rlx64(sp + 64); st[2] = ld_rlx64(sp + 8); st[3] = ld_rlx64(sp + 72);
                } while (__any_sync(0xFFFFFFFFu, (((st[0].y ^ tag) | (st[1].y ^ tag) | (st[2].y ^ tag) | (st[3].y ^ tag)) & 0xFFFFu) != 0) &&
                         ++it < SPIN_LIMIT);
#pragma unroll
                for (int rh = 0; rh < 2; rh++) {
                    const float ma = __uint_as_float(st[2 * rh].x & ~255u), mb = __uint_as_float(st[2 * rh + 1].x & ~255u);
                    const float mean = quad_sum(ma + mb) * 0.125f;
                    const float e2 = quad_sum(__uint_as_float(prmt(st[2 * rh].y, st[2 * rh].x, 0x3244)) +
                                              __uint_as_float(prmt(st[2 * rh + 1].y, st[2 * rh + 1].x, 0x3244)) + 56.f * (ma * ma + mb * mb));
                    const float m2 = fmaxf(fmaf(-448.f * mean, mean, e2), 0.f);
                    const float rs = bf_lo(pack2(rsqrtf(m2 * (1.0f / DM) + 1e-5f), 0.f));
                    rn[rh][0] = pack2(rs, rs);
                    rn[rh][1] = pack2(-mean * rs, -mean * rs);
                }
            }
            pin(rn[0], rn[1]);
            mbar_wait(BAR(F_Y0) + 8 * w, 0);
            TS(15);
            float acc[32];
            auto ln2_half = [&](auto HC) {
                constexpr int st = decltype(HC)::value;
                uint4 v[4][4];
                landed_read<st>(v, land, land_x, scr->x2 + (size_t)tile * 4096 + t, tag);
                if (st == 1 && lane == 0) mbar_arrive(BAR(R_Y0) + 8 * w);
                uint32_t cw[28], sw[28];
#pragma unroll
                for (int s = 0; s < 4; s++) {
                    uint32_t rr[14];
                    unpack14(v[s], rr);
#pragma unroll
                    for (int i = 0; i < 7; i++) {
                        const int blk = 7 * s + i;
                        if ((blk & 3) == 0) {
                            const uint32_t o = (7 * st + (blk >> 2)) * 64 + q * 16;
                            const uint4 c4 = lds128(SB + OFF_C2 + o), s4 = lds128(SB + OFF_S2 + o);
                            cw[blk] = c4.x; cw[blk + 1] = c4.y; cw[blk + 2] = c4.z; cw[blk + 3] = c4.w;
                            sw[blk] = s4.x; sw[blk + 1] = s4.y; sw[blk + 2] = s4.z; sw[blk + 3] = s4.w;
                        }
                        const int ks = 14 * st + 7 * (s >> 1) + (i == 6 ? 6 : 3 * (s & 1) + (i >> 1));
                        const int hi = i == 6 ? (s & 1) : (i & 1);
                        af[ks][2 * hi] = hfma2(hfma2(rr[2 * i], rn[0][0], rn[0][1]), cw[blk], sw[blk]);
                        af[ks][2 * hi + 1] = hfma2(hfma2(rr[2 * i + 1], rn[1][0], rn[1][1]), cw[blk], sw[blk]);
                    }
                }
#pragma unroll
                for (int s = 0; s < 14; s++) pin(af[14 * st + s]);
                const uint32_t sa = ring_get(IC<st>{});
                WG_FENCE();
#pragma unroll
                for (int s = 0; s < 14; s++)
                    wgmma_n64_t1(acc, af[14 * st + s],
                                 mk_desc16(sa, ((s / 7) * 14 + kstep_group<6>(s % 7)) * 512, SLOT / 2, 512 * kstep_gap(s % 7), 2),
                                 (st | s) != 0);
                WG_COMMIT();
            };
            ln2_half(IC<0>{});
            TS(8);
            ln2_half(IC<1>{});
            WG_WAIT(1);
            ring_put(IC<0>{});
            WG_WAIT(0);
            pin(acc);
            ring_put(IC<1>{});
            uint32_t hp[8];
#pragma unroll
            for (int i = 0; i < 8; i++) hp[i] = reglu2(acc[2 * i], acc[2 * i + 1], acc[16 + 2 * i], acc[17 + 2 * i]);
            sts128(hs + 4 * 2048, hp[0], hp[1], hp[2], hp[3]);
            sts128(hs + 5 * 2048, hp[4], hp[5], hp[6], hp[7]);
        }
        const uint32_t rwin = cta_win() ^ (1u << 24);
        const uint32_t hdst = rwin + SLOTA(0) + w * SLOT + t * 16, hbar = rwin + BAR(F_H0) + 8 * w;
        auto big_pass = [&](auto PC) {
            constexpr int p = decltype(PC)::value;
            float acc[64];
            auto stage = [&](auto SC_) {
                constexpr int st = decltype(SC_)::value;
                const uint32_t sa = ring_get(IC<2 + 4 * p + st>{});
                WG_FENCE();
#pragma unroll
                for (int s = 0; s < 7; s++)
                    wgmma_n128_t1(acc, af[7 * st + s], mk_desc16(sa, kstep_group<6>(s) * 1024, SLOT / 2, 1024 * kstep_gap(s), 1), (st | s) != 0);
                WG_COMMIT();
                if (p == 1 && st > 0) {
                    if (st == 1) mbar_wait_cluster(BAR(R_PR), 0);
#pragma unroll
                    for (int k = 2 * st - 2; k < 2 * st; k++) {
                        const uint4 hv = lds128(hs + k * 2048);
                        st_async128(hdst + (k < 4 ? k : k + 8) * 2048, hbar, hv.x, hv.y, hv.z, hv.w);
                    }
                }
                if constexpr (p == 2) st_async128(hdst + (4 + st) * 2048, hbar, hh[4 + st][0], hh[4 + st][1], hh[4 + st][2], hh[4 + st][3]);
                if (st > 0) {
                    WG_WAIT(1);
                    ring_put(IC<1 + 4 * p + st>{});
                }
            };
            stage(IC<0>{}); stage(IC<1>{}); stage(IC<2>{}); stage(IC<3>{});
            WG_WAIT(0);
            pin(acc);
            ring_put(IC<5 + 4 * p>{});
#pragma unroll
            for (int i = 0; i < 16; i++)
                hh[4 * p + (i >> 2)][i & 3] = reglu2(acc[2 * i], acc[2 * i + 1], acc[32 + 2 * i], acc[33 + 2 * i]);
            if (p == 0) {
#pragma unroll
                for (int k = 0; k < 4; k++) sts128(hs + k * 2048, hh[k][0], hh[k][1], hh[k][2], hh[k][3]);
            }
        };
        big_pass(IC<0>{});
        big_pass(IC<1>{});
        big_pass(IC<2>{});
#pragma unroll
        for (int k = 0; k < 6; k++) {
            const uint4 hv = lds128(hs + k * 2048);
            const int ks = k < 4 ? k : k + 8;
            hh[ks][0] = hv.x; hh[ks][1] = hv.y; hh[ks][2] = hv.z; hh[ks][3] = hv.w;
        }
#pragma unroll
        for (int s = 0; s < 14; s++) pin(hh[s]);
        TS(9);

        float accD[2][28], sum[28];
        uint4* pout_base = scr->part + (size_t)tile * 8 * 2048 + t;
        auto issue_pass = [&](float (&acc)[28], uint32_t (&a)[14][4], auto MC) {
            constexpr int m = decltype(MC)::value, par = (0xAC >> m) & 1;
            const uint32_t odd = par ? 1 - jo : jo;
            uint32_t base = ring_get(IC<14 + m>{}) + jo;
            asm volatile("" : "+r"(base));
            const uint32_t bb = base + odd * 256, bs = base - odd * 1536;
            WG_FENCE();
#pragma unroll
            for (int s = 0; s < 14; s++) wgmma_n56_t1(acc, a[s], mk_desc16(s < 12 ? bb : bs, s * 2048, 0, 1024, 1), par || s != 0);
            WG_COMMIT();
        };
        auto send = [&](float (&acc)[28], int k) {
            pin(acc);
            uint32_t pb[14];
#pragma unroll
            for (int i = 0; i < 14; i++) pb[i] = pack2(acc[2 * i], acc[2 * i + 1]);
            publish14(pout_base + ((j + 2 * k + 2) & 7) * 2048 + k * 512, pb, tag);
            if (lane == 0) st_rlx64(scr->hint + (64 + tile * 8 + ((j + 2 * k + 2) & 7)) * 8 * HS + k * HS + warp, tag, tag);
        };
        issue_pass(accD[0], hh, IC<0>{});
#pragma unroll
        for (int k = 8; k < 12; k++) st_async128(hdst + k * 2048, hbar, hh[k][0], hh[k][1], hh[k][2], hh[k][3]);
        issue_pass(accD[1], hh, IC<1>{});
        WG_WAIT(1);
        ring_put(IC<14>{});
        uint32_t hp[14][4];
        mbar_wait_cluster(BAR(F_H0) + 8 * w, 0);
#pragma unroll
        for (int s = 0; s < 14; s++) {
            const uint4 hv = lds128(SLOTA(0) + w * SLOT + s * 2048 + t * 16);
            hp[s][0] = hv.x; hp[s][1] = hv.y; hp[s][2] = hv.z; hp[s][3] = hv.w;
            pin(hp[s]);
        }
        __syncwarp();
        if (lane == 0) mbar_arrive(BAR(R_H0) + 8 * w);
        TS(27);
        issue_pass(accD[0], hp, IC<2>{});
        WG_WAIT(1);
        ring_put(IC<15>{});
        issue_pass(accD[1], hp, IC<3>{});
        WG_WAIT(1);
        ring_put(IC<16>{});
        send(accD[0], 0);
        issue_pass(accD[0], hh, IC<4>{});
        WG_WAIT(1);
        send(accD[1], 1);
        issue_pass(accD[0], hp, IC<5>{});
        issue_pass(accD[1], hh, IC<6>{});
        WG_WAIT(1);
        send(accD[0], 2);
        issue_pass(accD[1], hp, IC<7>{});
        TS(10);
        float gbf[14];
#pragma unroll
        for (int i = 0; i < 7; i++) {
            const uint32_t g = lds32(SB + OFF_GB + (4 * i + q) * 4);
            gbf[2 * i] = bf_lo(g); gbf[2 * i + 1] = bf_hi(g);
        }
        __nv_bfloat16* o0 = out + (size_t)(64 * tile + 16 * warp + lane / 7) * DM + 56 * j + (lane % 7) * 8;
        uint32_t stg = (warp < 2 ? SLOTA(0) + w * SLOT + 24576 : SB + OFF_QX + (w ? 0 : 12288) + 8192) + (warp & 1) * 1792;
        asm volatile("" : "+l"(o0), "+r"(stg));
        WG_WAIT(0);
        pin(accD[1]);
#pragma unroll
        for (int i = 0; i < 28; i++) sum[i] = gbf[2 * (i >> 2) + (i & 1)] * accD[1][i];
#pragma unroll 1
        for (int kk = 0; kk < 4; kk++) {
            const int k = (kk + 3) & 3;
            float gm[14];
#pragma unroll
            for (int i = 0; i < 14; i++) gm[i] = kk ? gbf[i] : 1.0f;
            const uint32_t la = (k < 3 ? SLOTA(0) + w * SLOT + k * 8192 : SB + OFF_QX + (w ? 0 : 12288)) + t * 16;
            const uint4* src = (k < 3 ? scr->part + ((size_t)tile * 8 + j) * 2048 + k * 512 : scr->x2 + ((size_t)tile * 8 + j) * 512) + t;
            pin(gm);
            mbar_wait(BAR(F_P) + 8 * (4 * w + k), 0);
            uint4 xv[4];
#pragma unroll
            for (int i = 0; i < 4; i++) xv[i] = lds128(la + i * 2048);
            int it = 0;
#pragma unroll 1
            while (__builtin_expect(__any_sync(0xFFFFFFFFu, tag_bad(xv, tag) != 0), 0)) {
#pragma unroll
                for (int i = 0; i < 4; i++) xv[i] = ld_rlx128(src + i * 128);
                if (++it > SPIN_LIMIT) break;
            }
            uint32_t rr[14];
            unpack14(xv, rr);
#pragma unroll
            for (int i = 0; i < 14; i++) {
                sum[2 * i] = fmaf(gm[2 * (i >> 1)], bf_lo(rr[i]), sum[2 * i]);
                sum[2 * i + 1] = fmaf(gm[2 * (i >> 1) + 1], bf_hi(rr[i]), sum[2 * i + 1]);
            }
        }
        {
            const uint32_t sa = stg + ((lane & 7) + (lane & 8)) * 112 + (lane >> 4) * 16;
#pragma unroll
            for (int i = 0; i < 3; i++)
                stsm4(sa + i * 32, pack2(sum[8 * i], sum[8 * i + 1]), pack2(sum[8 * i + 2], sum[8 * i + 3]), pack2(sum[8 * i + 4], sum[8 * i + 5]),
                      pack2(sum[8 * i + 6], sum[8 * i + 7]));
            stsm2(stg + (lane & 15) * 112 + 96, pack2(sum[24], sum[25]), pack2(sum[26], sum[27]));
            __syncwarp();
            if (lane < 28) {
#pragma unroll
                for (int i = 0; i < 4; i++) {
                    const uint4 v = lds128(stg + lane * 16 + i * 448);
                    asm volatile("st.global.v4.u32 [%0], {%1,%2,%3,%4};" ::"l"(o0 + i * 4 * DM), "r"(v.x), "r"(v.y), "r"(v.z), "r"(v.w) : "memory");
                }
            }
        }
        TS(11);
        TG(31);
    }
}

typedef CUresult (*EncodeFn)(CUtensorMap*, CUtensorMapDataType, cuuint32_t, void*, const cuuint64_t*, const cuuint64_t*,
                             const cuuint32_t*, const cuuint32_t*, CUtensorMapInterleave, CUtensorMapSwizzle,
                             CUtensorMapL2promotion, CUtensorMapFloatOOBfill);

void make_map_2d(EncodeFn enc, CUtensorMap* m, const void* ptr, uint64_t cols, uint64_t rows, uint32_t bc, uint32_t br,
                 CUtensorMapSwizzle swz) {
    cuuint64_t dims[2] = {cols, rows};
    cuuint64_t strides[1] = {cols * 2};
    cuuint32_t box[2] = {bc, br};
    cuuint32_t es[2] = {1, 1};
    enc(m, CU_TENSOR_MAP_DATA_TYPE_BFLOAT16, 2, const_cast<void*>(ptr), dims, strides, box, es, CU_TENSOR_MAP_INTERLEAVE_NONE, swz,
        CU_TENSOR_MAP_L2_PROMOTION_L2_128B, CU_TENSOR_MAP_FLOAT_OOB_FILL_NONE);
}

}

extern "C" void kernel_launch(void* const* d_in, const int* in_sizes, int n_in, void* d_out, int out_size) {
    (void)in_sizes; (void)n_in; (void)out_size;
    const __nv_bfloat16* x = (const __nv_bfloat16*)d_in[0];
    const __nv_bfloat16* wqkv = (const __nv_bfloat16*)d_in[1];
    const __nv_bfloat16* wo = (const __nv_bfloat16*)d_in[2];
    const __nv_bfloat16* wg = (const __nv_bfloat16*)d_in[4];
    const __nv_bfloat16* wu = (const __nv_bfloat16*)d_in[5];
    const __nv_bfloat16* wd = (const __nv_bfloat16*)d_in[6];
    const __nv_bfloat16* cv = (const __nv_bfloat16*)d_in[7];
    const __nv_bfloat16* wm = (const __nv_bfloat16*)d_in[8];

    void* fn = nullptr;
    cudaDriverEntryPointQueryResult qr;
    cudaGetDriverEntryPoint("cuTensorMapEncodeTiled", &fn, cudaEnableDefault, &qr);
    EncodeFn enc = (EncodeFn)fn;

    CUtensorMap tx, tq, two, tg, tu, tg3, tu3, td, tmm, tr;
    make_map_2d(enc, &tr, x, DM, SEQ, 64, 64, CU_TENSOR_MAP_SWIZZLE_128B);
    make_map_2d(enc, &tmm, wm, 6 * DM, DM, 16, 224, CU_TENSOR_MAP_SWIZZLE_NONE);
    make_map_2d(enc, &tx, x, DM, SEQ, 64, 128, CU_TENSOR_MAP_SWIZZLE_128B);
    make_map_2d(enc, &tq, wqkv, 3 * DM, DM, 64, 224, CU_TENSOR_MAP_SWIZZLE_128B);
    make_map_2d(enc, &two, wo, DM, DM, 64, 224, CU_TENSOR_MAP_SWIZZLE_128B);
    make_map_2d(enc, &tg, wg, FF, DM, 64, 112, CU_TENSOR_MAP_SWIZZLE_128B);
    make_map_2d(enc, &tu, wu, FF, DM, 64, 112, CU_TENSOR_MAP_SWIZZLE_128B);
    make_map_2d(enc, &tg3, wg, FF, DM, 32, 224, CU_TENSOR_MAP_SWIZZLE_64B);
    make_map_2d(enc, &tu3, wu, FF, DM, 32, 224, CU_TENSOR_MAP_SWIZZLE_64B);
    make_map_2d(enc, &td, wd, DM, FF, 64, 224, CU_TENSOR_MAP_SWIZZLE_128B);

    cudaFuncSetAttribute(fused_block_kernel, cudaFuncAttributeMaxDynamicSharedMemorySize, SMEM_BYTES);
    void* scr = nullptr;
    cudaGetSymbolAddress(&scr, g_scr);
    fused_block_kernel<<<NCTA, NTHREADS, SMEM_BYTES>>>((Scratch*)scr, x, cv, wm, (__nv_bfloat16*)d_out, wqkv, wo, wg, wu, wd, tx, tq, two, tg,
                                                       tu, tg3, tu3, td, tmm, tr);
}
```
